```python
import torch

def _softmax(x, axis=-1):
    return torch.softmax(x, dim=axis)

def _gelu(x):
    return torch.nn.functional.gelu(x, approximate='tanh')

def _silu(x):
    return torch.nn.functional.silu(x)

def _sigmoid(x):
    return torch.sigmoid(x)

def _layernorm(x, axis=-1, eps=1e-05):
    m = x.mean(dim=axis, keepdim=True)
    v = x.var(dim=axis, keepdim=True, unbiased=False)
    return (x - m) / torch.sqrt(v + eps)

def _scatter_add(tgt, idx, src, axis=0):
    return tgt.clone().index_add_(axis, idx, src)

def _segment_sum(src, seg, n):
    out = torch.zeros((n,) + src.shape[1:], dtype=src.dtype)
    return out.index_add_(0, seg, src)

def _pad(x, pw):
    flat = tuple((v for pair in reversed(pw) for v in pair))
    return torch.nn.functional.pad(x, flat)
kernel_name = 'gated_mix__memory_aug_recurrent_mem_tr__glu_gated_bilinear__prompt'

def setup_inputs():

    _w = lambda a: (lambda t: t.to(torch.bfloat16) if t.is_floating_point() else t)(torch.as_tensor(a))

    def _A_setup():
        B, S, Dm = (1, 2048, 640)
        H, Dh = (32, 128)
        M, seg = (8, 32)
        seg = min(seg, S)
        S = S // seg * seg
        return {'x': _w((lambda *s: torch.randn(*s, dtype=torch.bfloat16) * 0.05)(B, S, Dm)), 'mem0': _w((lambda *s: torch.randn(*s, dtype=torch.bfloat16) * 0.4)(B, M, Dm)), 'Wq': _w((lambda *s: torch.randn(*s, dtype=torch.bfloat16) * 6.4)(Dm, H, Dh) * Dm ** (-0.5)), 'Wk': _w((lambda *s: torch.randn(*s, dtype=torch.bfloat16) * 6.4)(Dm, H, Dh) * Dm ** (-0.5)), 'Wv': _w((lambda *s: torch.randn(*s, dtype=torch.bfloat16) * 0.4)(Dm, H, Dh) * Dm ** (-0.5)), 'Wo': _w((lambda *s: torch.randn(*s, dtype=torch.bfloat16) * 0.4)(H, Dh, Dm) * (H * Dh) ** (-0.5)), 'seg_len': seg}
    _A_in = _A_setup()

    def _B_setup():
        B, S, D, F = (1, 2048, 640, 1728)
        return {'x': _w((lambda *s: torch.randn(*s, dtype=torch.bfloat16) * 0.05)(B, S, D)), 'w_gate': _w((lambda *s: torch.randn(*s, dtype=torch.bfloat16) * 1.6)(D, F) * D ** (-0.5)), 'w_up': _w((lambda *s: torch.randn(*s, dtype=torch.bfloat16) * 1.6)(D, F) * D ** (-0.5)), 'w_down': _w((lambda *s: torch.randn(*s, dtype=torch.bfloat16) * 1.6)(F, D) * F ** (-0.5))}
    _B_in = _B_setup()
    return {'A_x': _A_in['x'], 'A_mem0': _A_in['mem0'], 'A_Wq': _A_in['Wq'], 'A_Wk': _A_in['Wk'], 'A_Wv': _A_in['Wv'], 'A_Wo': _A_in['Wo'], 'A_seg_len': _A_in['seg_len'], 'B_x': _B_in['x'], 'B_w_gate': _B_in['w_gate'], 'B_w_up': _B_in['w_up'], 'B_w_down': _B_in['w_down'], 'gate_w': _w((lambda *s: torch.randn(*s, dtype=torch.bfloat16) * 0.05)(640) * 16.0)}

def reference(A_x, A_mem0, A_Wq, A_Wk, A_Wv, A_Wo, A_seg_len, B_x, B_w_gate, B_w_up, B_w_down, gate_w):

    def _A_ref(x, mem0, Wq, Wk, Wv, Wo, seg_len):
        B, S, Dm = x.shape
        H, Dh = (Wq.shape[1], Wq.shape[2])
        M = mem0.shape[1]
        scale = Dh ** (-0.5)
        n_seg = S // seg_len
        L = M + seg_len
        idx = torch.arange(L)
        mask = (idx[:, None] < M) | (idx[:, None] >= idx[None, :])
        mem = mem0
        outs = []
        for s in range(n_seg):
            xs = x[:, s * seg_len:(s + 1) * seg_len, :].clone()
            h = torch.concatenate([mem, xs], axis=1)
            q = torch.einsum('btd,dhe->bhte', h, Wq)
            k = torch.einsum('btd,dhe->bhte', h, Wk)
            v = torch.einsum('btd,dhe->bhte', h, Wv)
            scores = torch.einsum('bhqe,bhke->bhqk', q, k) * scale
            scores = torch.where(mask[None, None], scores, -1000000000.0)
            p = _softmax(scores, axis=-1)
            o = torch.einsum('bhqk,bhke->bhqe', p, v)
            o = torch.einsum('bhte,hed->btd', o, Wo)
            mem = o[:, :M, :].clone()
            outs.append(o[:, M:, :])
        return torch.concatenate(outs, axis=1)

    def _B_ref(x, w_gate, w_up, w_down):
        g = torch.einsum('bsd,df->bsf', x, w_gate)
        u = torch.einsum('bsd,df->bsf', x, w_up)
        h = g * u
        return torch.einsum('bsf,fd->bsd', h, w_down)
    x = A_x
    g = _sigmoid((x * gate_w).sum(-1, keepdims=True))
    a = _A_ref(x, A_mem0, A_Wq, A_Wk, A_Wv, A_Wo, A_seg_len)
    b = _B_ref(x, B_w_gate, B_w_up, B_w_down)
    return g * a + (1 - g) * b
```

```cpp
#include <cuda_runtime.h>
#include <cuda_bf16.h>
#include <cuda.h>
#include <stdint.h>

typedef __nv_bfloat16 bf16;

constexpr int S_TOK = 2048, DM = 640, NH = 32, DH = 128, NMEM = 8, SEG = 32, NSEG = 64, FF = 1728;
constexpr int KC_O = 64, KC_H = 27, KC_ALL = 91;

__device__ __align__(1024) uint32_t g_act[16 * KC_ALL * 4096];
constexpr int ACC_LINE = 24;
constexpr int ACC_SLOT = 96 * ACC_LINE;
__device__ __align__(1024) uint4 g_acc[16 * ACC_SLOT];
__device__ unsigned g_start;
constexpr int QKV_ITEM = 7680;
__device__ __align__(1024) uint32_t g_qkv[NSEG * NH * QKV_ITEM];
__device__ unsigned g_qready[NSEG];

__device__ __forceinline__ uint32_t smem_u32(const void* p) { return (uint32_t)__cvta_generic_to_shared(p); }
__device__ __forceinline__ uint32_t mapa(uint32_t a, uint32_t r) { uint32_t o; asm("mapa.shared::cluster.u32 %0, %1, %2;" : "=r"(o) : "r"(a), "r"(r)); return o; }
__device__ __forceinline__ void mbar_init(uint32_t b, int c) { asm volatile("mbarrier.init.shared::cta.b64 [%0], %1;" ::"r"(b), "r"(c) : "memory"); }
__device__ __forceinline__ void mbar_expect(uint32_t b, int bytes) { asm volatile("mbarrier.arrive.expect_tx.shared::cta.b64 _, [%0], %1;" ::"r"(b), "r"(bytes) : "memory"); }
__device__ __forceinline__ void mbar_arrive(uint32_t b) { asm volatile("mbarrier.arrive.shared::cta.b64 _, [%0];" ::"r"(b) : "memory"); }
__device__ __forceinline__ void mbar_wait(uint32_t b, int par) {
    asm volatile("{\n\t.reg .pred p;\n\t.reg .u32 n;\n\tmov.u32 n, 0;\n"
                 "WAIT_LOOP:\n\tmbarrier.try_wait.parity.shared::cta.b64 p, [%0], %1;\n\t@p bra.uni WAIT_DONE;\n\t"
                 "add.u32 n, n, 1;\n\tsetp.lt.u32 p, n, 4194304;\n\t@p bra.uni WAIT_LOOP;\n\ttrap;\n"
                 "WAIT_DONE:\n\t}" ::"r"(b), "r"(par) : "memory");
}
__device__ __forceinline__ void mbar_wait_cl(uint32_t b, int par) {
    asm volatile("{\n\t.reg .pred p;\n\t.reg .u32 n;\n\tmov.u32 n, 0;\n"
                 "WAIT_LOOP:\n\tmbarrier.try_wait.parity.relaxed.cluster.shared::cta.b64 p, [%0], %1;\n\t@p bra.uni WAIT_DONE;\n\t"
                 "add.u32 n, n, 1;\n\tsetp.lt.u32 p, n, 4194304;\n\t@p bra.uni WAIT_LOOP;\n\ttrap;\n"
                 "WAIT_DONE:\n\tfence.acquire.sync_restrict::shared::cluster.cluster;\n\t}" ::"r"(b), "r"(par) : "memory");
}
__device__ __forceinline__ void cluster_sync_relaxed() { asm volatile("barrier.cluster.arrive.relaxed.aligned; barrier.cluster.wait.aligned;" ::: "memory"); }
__device__ __forceinline__ void cluster_sync_all() { asm volatile("barrier.cluster.arrive.aligned; barrier.cluster.wait.aligned;" ::: "memory"); }
template <int ID, int N> __device__ __forceinline__ void bar_sync() { asm volatile("bar.sync %0, %1;" ::"n"(ID), "n"(N) : "memory"); }
template <int ID, int N> __device__ __forceinline__ void bar_arrive() { asm volatile("bar.arrive %0, %1;" ::"n"(ID), "n"(N) : "memory"); }
__device__ __forceinline__ void bar_sync_r(int id, int n) { asm volatile("bar.sync %0, %1;" ::"r"(id), "r"(n) : "memory"); }
__device__ __forceinline__ void fence_proxy_async() { asm volatile("fence.proxy.async.shared::cta;" ::: "memory"); }
__device__ __forceinline__ void fence_release_gpu() { asm volatile("fence.release.gpu;" ::: "memory"); }
__device__ __forceinline__ void red_add_gpu(unsigned* p) { asm volatile("red.relaxed.gpu.global.add.u32 [%0], 1;" ::"l"(p) : "memory"); }
__device__ __forceinline__ void tma3d_mc(uint32_t dst, const CUtensorMap* m, int c1, int c2, uint32_t bar, uint16_t mask) {
    asm volatile("cp.async.bulk.tensor.3d.shared::cluster.global.mbarrier::complete_tx::bytes.multicast::cluster [%0], [%1, {%3, %4, %5}], [%2], %6;"
                 ::"r"(dst), "l"(m), "r"(bar), "r"(0), "r"(c1), "r"(c2), "h"(mask) : "memory");
}
__device__ __forceinline__ void tma2d(uint32_t dst, const CUtensorMap* m, int c0, int c1, uint32_t bar) {
    asm volatile("cp.async.bulk.tensor.2d.shared::cluster.global.mbarrier::complete_tx::bytes [%0], [%1, {%3, %4}], [%2];"
                 ::"r"(dst), "l"(m), "r"(bar), "r"(c0), "r"(c1) : "memory");
}
__device__ __forceinline__ void tma2d_mc(uint32_t dst, const CUtensorMap* m, int c0, int c1, uint32_t bar, uint16_t mask) {
    asm volatile("cp.async.bulk.tensor.2d.shared::cluster.global.mbarrier::complete_tx::bytes.multicast::cluster [%0], [%1, {%3, %4}], [%2], %5;"
                 ::"r"(dst), "l"(m), "r"(bar), "r"(c0), "r"(c1), "h"(mask) : "memory");
}
__device__ __forceinline__ void tma2d_prefetch(const CUtensorMap* m, int c0, int c1) {
    asm volatile("cp.async.bulk.prefetch.tensor.2d.L2.global [%0, {%1, %2}];" ::"l"(m), "r"(c0), "r"(c1) : "memory");
}
__device__ __forceinline__ void bulk_s2c(uint32_t dst, uint32_t src, int bytes, uint32_t bar) {
    asm volatile("cp.async.bulk.shared::cluster.shared::cta.mbarrier::complete_tx::bytes [%0], [%1], %2, [%3];" ::"r"(dst), "r"(src), "r"(bytes), "r"(bar) : "memory");
}
__device__ __forceinline__ void bulk_s2g(void* dst, uint32_t src, int bytes) {
    asm volatile("cp.async.bulk.global.shared::cta.bulk_group [%0], [%1], %2;\n\tcp.async.bulk.commit_group;" ::"l"(dst), "r"(src), "r"(bytes) : "memory");
}
__device__ __forceinline__ void ldsm4(uint32_t* r, uint32_t a) { asm volatile("ldmatrix.sync.aligned.m8n8.x4.shared.b16 {%0,%1,%2,%3}, [%4];" : "=r"(r[0]), "=r"(r[1]), "=r"(r[2]), "=r"(r[3]) : "r"(a) : "memory"); }
__device__ __forceinline__ void ldsm4t(uint32_t* r, uint32_t a) { asm volatile("ldmatrix.sync.aligned.m8n8.x4.trans.shared.b16 {%0,%1,%2,%3}, [%4];" : "=r"(r[0]), "=r"(r[1]), "=r"(r[2]), "=r"(r[3]) : "r"(a) : "memory"); }
__device__ __forceinline__ void stsm4(uint32_t a, uint32_t r0, uint32_t r1, uint32_t r2, uint32_t r3) { asm volatile("stmatrix.sync.aligned.m8n8.x4.shared.b16 [%0], {%1,%2,%3,%4};" ::"r"(a), "r"(r0), "r"(r1), "r"(r2), "r"(r3) : "memory"); }
__device__ __forceinline__ void lds128(uint32_t* r, uint32_t a) { asm volatile("ld.shared.v4.u32 {%0,%1,%2,%3}, [%4];" : "=r"(r[0]), "=r"(r[1]), "=r"(r[2]), "=r"(r[3]) : "r"(a) : "memory"); }
__device__ __forceinline__ void lds128f(float* r, uint32_t a) { asm volatile("ld.shared.v4.f32 {%0,%1,%2,%3}, [%4];" : "=f"(r[0]), "=f"(r[1]), "=f"(r[2]), "=f"(r[3]) : "r"(a) : "memory"); }
__device__ __forceinline__ void lds64(uint32_t* r, uint32_t a) { asm volatile("ld.shared.v2.u32 {%0,%1}, [%2];" : "=r"(r[0]), "=r"(r[1]) : "r"(a) : "memory"); }
__device__ __forceinline__ void lds64f(float* r, uint32_t a) { asm volatile("ld.shared.v2.f32 {%0,%1}, [%2];" : "=f"(r[0]), "=f"(r[1]) : "r"(a) : "memory"); }
__device__ __forceinline__ void lds128fv(float* r, uint32_t a) { asm volatile("ld.volatile.shared.v4.f32 {%0,%1,%2,%3}, [%4];" : "=f"(r[0]), "=f"(r[1]), "=f"(r[2]), "=f"(r[3]) : "r"(a) : "memory"); }
__device__ __forceinline__ void lds64fv(float* r, uint32_t a) { asm volatile("ld.volatile.shared.v2.f32 {%0,%1}, [%2];" : "=f"(r[0]), "=f"(r[1]) : "r"(a) : "memory"); }
__device__ __forceinline__ void sts128(uint32_t a, uint32_t r0, uint32_t r1, uint32_t r2, uint32_t r3) { asm volatile("st.shared.v4.u32 [%0], {%1,%2,%3,%4};" ::"r"(a), "r"(r0), "r"(r1), "r"(r2), "r"(r3) : "memory"); }
__device__ __forceinline__ void sts128f(uint32_t a, float r0, float r1, float r2, float r3) { asm volatile("st.shared.v4.f32 [%0], {%1,%2,%3,%4};" ::"r"(a), "f"(r0), "f"(r1), "f"(r2), "f"(r3) : "memory"); }
__device__ __forceinline__ void st_async4(uint32_t a, uint32_t r0, uint32_t r1, uint32_t r2, uint32_t r3, uint32_t bar) {
    asm volatile("st.async.shared::cluster.mbarrier::complete_tx::bytes.v4.u32 [%0], {%1,%2,%3,%4}, [%5];" ::"r"(a), "r"(r0), "r"(r1), "r"(r2), "r"(r3), "r"(bar) : "memory");
}
__device__ __forceinline__ void st_async4f(uint32_t a, float r0, float r1, float r2, float r3, uint32_t bar) {
    st_async4(a, __float_as_uint(r0), __float_as_uint(r1), __float_as_uint(r2), __float_as_uint(r3), bar);
}
__device__ __forceinline__ void mma16816(float* d, const uint32_t* a, uint32_t b0, uint32_t b1) {
    asm volatile("mma.sync.aligned.m16n8k16.row.col.f32.bf16.bf16.f32 {%0,%1,%2,%3}, {%4,%5,%6,%7}, {%8,%9}, {%0,%1,%2,%3};"
                 : "+f"(d[0]), "+f"(d[1]), "+f"(d[2]), "+f"(d[3]) : "r"(a[0]), "r"(a[1]), "r"(a[2]), "r"(a[3]), "r"(b0), "r"(b1));
}
__device__ __forceinline__ void mma16816z(float* d, const uint32_t* a, uint32_t b0, uint32_t b1) {
    asm volatile("mma.sync.aligned.m16n8k16.row.col.f32.bf16.bf16.f32 {%0,%1,%2,%3}, {%4,%5,%6,%7}, {%8,%9}, {%10,%10,%10,%10};"
                 : "=f"(d[0]), "=f"(d[1]), "=f"(d[2]), "=f"(d[3]) : "r"(a[0]), "r"(a[1]), "r"(a[2]), "r"(a[3]), "r"(b0), "r"(b1), "f"(0.f));
}
__device__ __forceinline__ void mma1688(float* d, uint32_t a0, uint32_t a1, uint32_t b0) {
    asm volatile("mma.sync.aligned.m16n8k8.row.col.f32.bf16.bf16.f32 {%0,%1,%2,%3}, {%4,%5}, {%6}, {%0,%1,%2,%3};"
                 : "+f"(d[0]), "+f"(d[1]), "+f"(d[2]), "+f"(d[3]) : "r"(a0), "r"(a1), "r"(b0));
}
__device__ __forceinline__ void mma1688z(float* d, uint32_t a0, uint32_t a1, uint32_t b0) {
    asm volatile("mma.sync.aligned.m16n8k8.row.col.f32.bf16.bf16.f32 {%0,%1,%2,%3}, {%4,%5}, {%6}, {%7,%7,%7,%7};"
                 : "=f"(d[0]), "=f"(d[1]), "=f"(d[2]), "=f"(d[3]) : "r"(a0), "r"(a1), "r"(b0), "f"(0.f));
}
__device__ __forceinline__ void bar_arrive_r(int id, int n) { asm volatile("bar.arrive %0, %1;" ::"r"(id), "r"(n) : "memory"); }
#define SCHED_FENCE() asm volatile("{\n\t.reg .pred p;\n\tsetp.eq.s32 p, %0, %1;\n\t@p trap;\n\t}" ::"r"(poll_delay), "n"(-1 - __COUNTER__) : "memory")
__device__ __forceinline__ uint32_t pack2(float lo, float hi) { uint32_t r; asm("cvt.rn.bf16x2.f32 %0, %1, %2;" : "=r"(r) : "f"(hi), "f"(lo)); return r; }
__device__ __forceinline__ float ex2(float x) { float y; asm("ex2.approx.ftz.f32 %0, %1;" : "=f"(y) : "f"(x)); return y; }
__device__ __forceinline__ float rcp(float x) { float y; asm("rcp.approx.ftz.f32 %0, %1;" : "=f"(y) : "f"(x)); return y; }
#define WG_FENCE() asm volatile("wgmma.fence.sync.aligned;" ::: "memory")
#define WG_COMMIT() asm volatile("wgmma.commit_group.sync.aligned;" ::: "memory")
#define WG_WAIT0() asm volatile("wgmma.wait_group.sync.aligned 0;" ::: "memory")
template <int SC>
__device__ __forceinline__ void wgmma_n32_rs(float* d, const uint32_t* a, uint64_t desc) {
    asm volatile("wgmma.mma_async.sync.aligned.m64n32k16.f32.bf16.bf16 {%0,%1,%2,%3,%4,%5,%6,%7,%8,%9,%10,%11,%12,%13,%14,%15}, {%16,%17,%18,%19}, %20, %21, 1, 1, 0;"
                 : "+f"(d[0]), "+f"(d[1]), "+f"(d[2]), "+f"(d[3]), "+f"(d[4]), "+f"(d[5]), "+f"(d[6]), "+f"(d[7]),
                   "+f"(d[8]), "+f"(d[9]), "+f"(d[10]), "+f"(d[11]), "+f"(d[12]), "+f"(d[13]), "+f"(d[14]), "+f"(d[15])
                 : "r"(a[0]), "r"(a[1]), "r"(a[2]), "r"(a[3]), "l"(desc), "n"(SC));
}
__device__ __forceinline__ void wgmma_n32_rs_z(float* d, const uint32_t* a, uint64_t desc) {
    asm volatile("wgmma.mma_async.sync.aligned.m64n32k16.f32.bf16.bf16 {%0,%1,%2,%3,%4,%5,%6,%7,%8,%9,%10,%11,%12,%13,%14,%15}, {%16,%17,%18,%19}, %20, 0, 1, 1, 0;"
                 : "=f"(d[0]), "=f"(d[1]), "=f"(d[2]), "=f"(d[3]), "=f"(d[4]), "=f"(d[5]), "=f"(d[6]), "=f"(d[7]),
                   "=f"(d[8]), "=f"(d[9]), "=f"(d[10]), "=f"(d[11]), "=f"(d[12]), "=f"(d[13]), "=f"(d[14]), "=f"(d[15])
                 : "r"(a[0]), "r"(a[1]), "r"(a[2]), "r"(a[3]), "l"(desc));
}
template <int SC>
__device__ __forceinline__ void wgmma_n24_tt(float* d, uint64_t da, uint64_t db) {
    asm volatile("wgmma.mma_async.sync.aligned.m64n24k16.f32.bf16.bf16 {%0,%1,%2,%3,%4,%5,%6,%7,%8,%9,%10,%11}, %12, %13, %14, 1, 1, 1, 1;"
                 : "+f"(d[0]), "+f"(d[1]), "+f"(d[2]), "+f"(d[3]), "+f"(d[4]), "+f"(d[5]), "+f"(d[6]), "+f"(d[7]),
                   "+f"(d[8]), "+f"(d[9]), "+f"(d[10]), "+f"(d[11])
                 : "l"(da), "l"(db), "n"(SC));
}
template <int SC>
__device__ __forceinline__ void wgmma_n32_ss(float* d, uint64_t da, uint64_t db) {
    asm volatile("wgmma.mma_async.sync.aligned.m64n32k16.f32.bf16.bf16 {%0,%1,%2,%3,%4,%5,%6,%7,%8,%9,%10,%11,%12,%13,%14,%15}, %16, %17, %18, 1, 1, 0, 0;"
                 : "+f"(d[0]), "+f"(d[1]), "+f"(d[2]), "+f"(d[3]), "+f"(d[4]), "+f"(d[5]), "+f"(d[6]), "+f"(d[7]),
                   "+f"(d[8]), "+f"(d[9]), "+f"(d[10]), "+f"(d[11]), "+f"(d[12]), "+f"(d[13]), "+f"(d[14]), "+f"(d[15])
                 : "l"(da), "l"(db), "n"(SC));
}
__device__ __forceinline__ void wgmma_n24_tt_z(float* d, uint64_t da, uint64_t db) {
    asm volatile("wgmma.mma_async.sync.aligned.m64n24k16.f32.bf16.bf16 {%0,%1,%2,%3,%4,%5,%6,%7,%8,%9,%10,%11}, %12, %13, 0, 1, 1, 1, 1;"
                 : "=f"(d[0]), "=f"(d[1]), "=f"(d[2]), "=f"(d[3]), "=f"(d[4]), "=f"(d[5]), "=f"(d[6]), "=f"(d[7]),
                   "=f"(d[8]), "=f"(d[9]), "=f"(d[10]), "=f"(d[11])
                 : "l"(da), "l"(db));
}
__device__ __forceinline__ void wgmma_n32_ss_z(float* d, uint64_t da, uint64_t db) {
    asm volatile("wgmma.mma_async.sync.aligned.m64n32k16.f32.bf16.bf16 {%0,%1,%2,%3,%4,%5,%6,%7,%8,%9,%10,%11,%12,%13,%14,%15}, %16, %17, 0, 1, 1, 0, 0;"
                 : "=f"(d[0]), "=f"(d[1]), "=f"(d[2]), "=f"(d[3]), "=f"(d[4]), "=f"(d[5]), "=f"(d[6]), "=f"(d[7]),
                   "=f"(d[8]), "=f"(d[9]), "=f"(d[10]), "=f"(d[11]), "=f"(d[12]), "=f"(d[13]), "=f"(d[14]), "=f"(d[15])
                 : "l"(da), "l"(db));
}
__device__ __forceinline__ uint64_t mkdesc(uint32_t addr, uint32_t lbo, uint32_t sbo) {
    return (uint64_t)((addr & 0x3FFFF) >> 4) | ((uint64_t)(lbo >> 4) << 16) | ((uint64_t)(sbo >> 4) << 32);
}
__device__ __forceinline__ int clk32() { unsigned long long t; asm volatile("mov.u64 %0, %%clock64;" : "=l"(t)::"memory"); return (int)t; }
__device__ __forceinline__ void spin_until(int t1, const void* keep) {
    asm volatile("{\n\t.reg .pred p;\n\t.reg .u64 t;\n\t.reg .s32 a, b;\n"
                 "SPIN:\n\tmov.u64 t, %%clock64;\n\tcvt.u32.u64 a, t;\n\tsub.s32 b, a, %0;\n\tsetp.lt.s32 p, b, 0;\n\t@p bra.uni SPIN;\n\t}" ::"r"(t1), "l"(keep) : "memory");
}

constexpr int R_XB = 0;
constexpr int R_WO = 81920;
constexpr int R_VT = 147456;
constexpr int R_QK = 167936;
constexpr int R_VS = R_QK;
constexpr int R_QS = 188416;
constexpr int R_MEM = 190464;
constexpr int R_VM = 201216;
constexpr int R_SMSG = 203264;
constexpr int R_OB = 206336;
constexpr int R_SUM = R_OB + 2048;
constexpr int R_EX = 208896;
constexpr int R_BAR = 217088;
constexpr int R_WST = 40960;
constexpr int R_SMEM = 217344 + 1024 + 6656;
enum { B_W0 = 0, B_X0 = 4, B_WO = 6, B_S = 7, B_V = 8, B_VX = 9, B_XF = 10, B_NUM = 11 };
enum { NB_MEM = 1, NB_QK = 2, NB_O = 3, NB_EX = 4, NB_EPI = 6, NB_SENT = 7, NB_PAIR = 8, NB_VC = 12 };
#define POLL_DELAY 1050
#define TS(i)
#define TSD(i, dep)

__device__ __forceinline__ uint32_t pin(uint32_t v) { return __shfl_sync(~0u, v, threadIdx.x & 31); }
__device__ __forceinline__ void st_async2f(uint32_t a, float r0, float r1, uint32_t bar) {
    asm volatile("st.async.shared::cluster.mbarrier::complete_tx::bytes.v2.f32 [%0], {%1,%2}, [%3];" ::"r"(a), "f"(r0), "f"(r1), "r"(bar) : "memory");
}

#define GK1 20
#define GK2 8
#define GK3 20
#define XMODE 2
__device__ __forceinline__ void xload(const uint32_t sb, const CUtensorMap* tmX, int s, int rank, int head) {
    mbar_expect(sb + R_BAR + 8 * (B_X0 + (s & 1)), 40960);
    if (rank < 2) {
        tma3d_mc(sb + R_XB + (s & 1) * 40960 + rank * 20480, tmX, (s + 2) * SEG, rank * 5, sb + R_BAR + 8 * (B_X0 + (s & 1)), 7);
        if (head == (s & 31) && s + 4 < NSEG)
            asm volatile("cp.async.bulk.prefetch.tensor.3d.L2.global [%0, {%1, %2, %3}];" ::"l"(tmX), "r"(0), "r"((s + 4) * SEG), "r"(rank * 5) : "memory");
    }
}

template <int RANK>
__device__ __forceinline__ void aux_loop(const uint32_t sb, const int head, const CUtensorMap* tmX, const int poll_delay) {
    constexpr bool ISV = RANK == 2;
    const uint32_t bars = sb + R_BAR;
    const float SC = 0.08838834764831845f * 1.4426950408889634f;
    const int w = __shfl_sync(~0u, (threadIdx.x >> 5) & 3, 0);
    uint32_t l16 = pin(sb + (threadIdx.x & 31) * 16);
#define LOCAL() asm volatile("" : "+r"(l16))
#define first (w == 0 && l16 == sb)
#define LANE ((l16 >> 4) & 31)
#define TSW (8 + w)
    uint32_t vto = 0;
    if (ISV) {
        bar_sync<NB_QK, 384>();
        if (first) {
            bulk_s2c(mapa(sb + R_VT, 0), sb + R_VT, 8192, mapa(bars + 8 * B_VX, 0));
            bulk_s2c(mapa(sb + R_VT, 1), sb + R_VT, 8192, mapa(bars + 8 * B_VX, 1));
        }
        __syncwarp();
    }
#pragma unroll 1
    for (int s = 0;; s++) {
        if (ISV || w == 3) bar_arrive<NB_MEM, 384>();
        else bar_sync<NB_MEM, 384>();
        LOCAL();
        if (first && s < NSEG - 1) {
            mbar_expect(bars + 8 * B_S, ISV ? 2560 : 1280);
            if (!ISV) { mbar_expect(bars + 8 * B_V, 2048); mbar_expect(bars + 8 * B_VX, 8192); }
        }
        __syncwarp();
        if (w == 3) {
            asm volatile("cp.async.bulk.wait_group 0;" ::: "memory");
            if ((s & 3) == 0 || s >= NSEG - 3) {
                asm volatile("fence.proxy.async.global;" ::: "memory");
                fence_release_gpu();
                if (LANE == 0 && s > 0) red_add_gpu(&g_qready[s - 1]);
                if ((s & 3) == 0) g_acc[((s + 5 + (LANE >> 3)) & 15) * ACC_SLOT + (head * 3 + RANK) * ACC_LINE + (LANE & 7)] = make_uint4(0, 0, 0, 0);
                if (RANK == 0 && s == 8 && head == 0 && LANE == 0) g_start = 0;
            }
            __syncwarp();
        }
        if (s == NSEG - 1) break;
        if (!ISV) mbar_wait_cl(bars + 8 * B_VX, s & 1);
        if (!ISV) {
            const uint32_t sbar = bars + 8 * B_S, sa = l16 + w * 512 + R_SMSG + RANK * 1536;
            if (w < 2) {
                uint32_t kf[4][4], qf[4][4];
#pragma unroll
                for (int k = 0; k < 4; k++) ldsm4t(kf[k], l16 + (s & 1) * 10240 + w * 512 + R_QK + 4096 + k * 1024);
                bar_sync<NB_QK, 352>();
#pragma unroll
                for (int k = 0; k < 4; k++) ldsm4t(qf[k], l16 + R_QS + k * 512);
                SCHED_FENCE();
                float e0[2][4], e1[2][4];
                mma16816z(e0[0], qf[0], kf[0][0], kf[0][1]); mma16816z(e1[0], qf[0], kf[0][2], kf[0][3]);
                mma16816z(e0[1], qf[1], kf[1][0], kf[1][1]); mma16816z(e1[1], qf[1], kf[1][2], kf[1][3]);
                mma16816(e0[0], qf[2], kf[2][0], kf[2][1]); mma16816(e1[0], qf[2], kf[2][2], kf[2][3]);
                mma16816(e0[1], qf[3], kf[3][0], kf[3][1]); mma16816(e1[1], qf[3], kf[3][2], kf[3][3]);
                const float v0 = (e0[0][0] + e0[0][2]) + (e0[1][0] + e0[1][2]), v1 = (e0[0][1] + e0[0][3]) + (e0[1][1] + e0[1][3]);
                const float v2 = (e1[0][0] + e1[0][2]) + (e1[1][0] + e1[1][2]), v3 = (e1[0][1] + e1[0][3]) + (e1[1][1] + e1[1][3]);
                st_async4f(mapa(sa, 1 - RANK), v0, v1, v2, v3, mapa(sbar, 1 - RANK));
                st_async4f(mapa(sa, 2), v0, v1, v2, v3, mapa(sbar, 2));
                sts128f(sa, v0, v1, v2, v3);
                __syncwarp();
                if (l16 == sb) mbar_arrive(sbar);
                TS(1);
            } else if (w == 2) {
                uint32_t kf[4][4], qf[4][4];
                bar_sync<NB_QK, 352>();
#pragma unroll
                for (int k = 0; k < 4; k++) { ldsm4t(qf[k], l16 + R_QS + k * 512); ldsm4t(kf[k], l16 + (s & 1) * 10240 + R_QK + 8192 + k * 512); }
                SCHED_FENCE();
                float e0[2][4], e1[2][4];
                mma16816z(e0[0], qf[0], kf[0][0], kf[0][1]); mma16816z(e1[0], qf[0], kf[0][2], kf[0][3]);
                mma16816z(e0[1], qf[1], kf[1][0], kf[1][1]); mma16816z(e1[1], qf[1], kf[1][2], kf[1][3]);
                mma16816(e0[0], qf[2], kf[2][0], kf[2][1]); mma16816(e1[0], qf[2], kf[2][2], kf[2][3]);
                mma16816(e0[1], qf[3], kf[3][0], kf[3][1]); mma16816(e1[1], qf[3], kf[3][2], kf[3][3]);
                const float v0 = ((e0[0][0] + e0[0][2]) + (e1[0][0] + e1[0][2])) + ((e0[1][0] + e0[1][2]) + (e1[1][0] + e1[1][2]));
                const float v1 = ((e0[0][1] + e0[0][3]) + (e1[0][1] + e1[0][3])) + ((e0[1][1] + e0[1][3]) + (e1[1][1] + e1[1][3]));
                st_async2f(mapa(sa, 1 - RANK), v0, v1, mapa(sbar, 1 - RANK));
                st_async2f(mapa(sa, 2), v0, v1, mapa(sbar, 2));
                asm volatile("st.shared.v2.f32 [%0], {%1,%2};" ::"r"(sa), "f"(v0), "f"(v1) : "memory");
                __syncwarp();
                if (l16 == sb) mbar_arrive(sbar);
                TS(1);
            }
        }
        uint32_t va[2][2][4], vm[4];
        {
            const uint32_t a = (l16 & ~0x180u) + ((l16 & 128) << 2) + ((l16 & 256) >> 1) + w * 1024 + vto + R_VT;
#pragma unroll
            for (int T = 0; T < 2; T++)
#pragma unroll
                for (int k = 0; k < 2; k++) ldsm4(va[T][k], a + T * 4096 + k * 256);
        }
        if (!ISV && w < 3) bar_arrive<NB_SENT, 352>();
        const uint32_t vma = (l16 & ~0x100u) + ((l16 & 256) << 2) + w * 256 + R_VT + 8192 + vto;
        if (ISV) { bar_sync<NB_QK, 384>(); ldsm4(vm, vma); }
        mbar_wait_cl(bars + 8 * B_S, s & 1);
        TS(2);
        float sv[10], b[10];
        lds128fv(sv, l16 + R_SMSG); lds128fv(b, l16 + R_SMSG + 1536);
        lds128fv(sv + 4, l16 + R_SMSG + 512); lds128fv(b + 4, l16 + R_SMSG + 2048);
        lds64fv(sv + 8, l16 + R_SMSG + 1024); lds64fv(b + 8, l16 + R_SMSG + 2560);
        SCHED_FENCE();
#pragma unroll
        for (int e = 0; e < 10; e++) sv[e] += b[e];
        float mx = fmaxf(fmaxf(fmaxf(sv[0], sv[1]), fmaxf(sv[2], sv[3])), fmaxf(fmaxf(sv[4], sv[5]), fmaxf(sv[6], sv[7])));
        mx = fmaxf(mx, fmaxf(sv[8], sv[9]));
        mx = fmaxf(mx, __shfl_xor_sync(~0u, mx, 1));
        uint32_t vok = 1;
        if (!ISV) asm volatile("{.reg .pred p; mbarrier.test_wait.parity.relaxed.cluster.shared::cta.b64 p, [%1], %2; selp.u32 %0, 1, 0, p;}" : "=r"(vok) : "r"(bars + 8 * B_V), "r"(s & 1) : "memory");
        mx = fmaxf(mx, __shfl_xor_sync(~0u, mx, 2));
        mx *= -SC;
        float oa[2][4], sm[4];
        {
            const uint32_t one = 0x3F803F80u;
            const uint32_t ones[4] = {one, one, one, one};
            if (!ISV) {
                if (!__all_sync(~0u, vok)) mbar_wait_cl(bars + 8 * B_V, s & 1);
                asm volatile("fence.acquire.sync_restrict::shared::cluster.cluster;" ::: "memory");
                ldsm4(vm, vma);
            }
            const uint32_t p0 = pack2(ex2(fmaf(sv[0], SC, mx)), ex2(fmaf(sv[1], SC, mx))), p1 = pack2(ex2(fmaf(sv[2], SC, mx)), ex2(fmaf(sv[3], SC, mx)));
            mma16816z(oa[0], va[0][0], p0, p1); mma16816z(oa[1], va[1][0], p0, p1); mma16816z(sm, ones, p0, p1);
            const uint32_t p4 = pack2(ex2(fmaf(sv[8], SC, mx)), ex2(fmaf(sv[9], SC, mx)));
            mma1688(oa[0], vm[0], vm[1], p4); mma1688(oa[1], vm[2], vm[3], p4); mma1688(sm, one, one, p4);
            const uint32_t p2 = pack2(ex2(fmaf(sv[4], SC, mx)), ex2(fmaf(sv[5], SC, mx))), p3 = pack2(ex2(fmaf(sv[6], SC, mx)), ex2(fmaf(sv[7], SC, mx)));
            mma16816(oa[0], va[0][1], p2, p3); mma16816(oa[1], va[1][1], p2, p3); mma16816(sm, ones, p2, p3);
        }
        stsm4(l16 + w * 512 + R_OB, pack2(oa[0][0], oa[0][1]), pack2(oa[0][2], oa[0][3]), pack2(oa[1][0], oa[1][1]), pack2(oa[1][2], oa[1][3]));
        if (w == 0) asm volatile("st.shared.v2.f32 [%0], {%1,%2};" ::"r"(l16 + R_SUM), "f"(sm[0]), "f"(sm[1]) : "memory");
        bar_sync<NB_O, 384>();
        TS(3);
        const int tO = clk32();
        vto = ISV ? (vto == 20480 ? 0 : vto + 10240) : 10240 - vto;
        const uint4* ap = g_acc + (s & 15) * ACC_SLOT + (w * 24 + (LANE >> 3)) * ACC_LINE + (LANE & 3) * 2 + ((LANE >> 2) & 1);
        const bool odd = (l16 >> 6) & 1;
        const uint32_t st1 = l16 + R_MEM + w * 2688 + (LANE >= 24 ? 384 : 0), st2 = l16 + R_MEM + w * 2688 + 384;
        spin_until(tO + poll_delay, ap);
        TS(4);
        int lim = 0;
        while (true) {
            uint4 a[6];
#pragma unroll
            for (int i = 0; i < 6; i++)
                asm volatile("ld.relaxed.gpu.global.v4.u32 {%0,%1,%2,%3}, [%4];" : "=r"(a[i].x), "=r"(a[i].y), "=r"(a[i].z), "=r"(a[i].w)
                             : "l"(ap + i * 4 * ACC_LINE) : "memory");
            if (ISV && lim == 0 && w < 2 && s + 1 < NSEG - 1) {
                if (l16 == sb) bulk_s2c(mapa(sb + R_VT + ((s + 1) & 1) * 10240, w), sb + R_VT + vto, 8192, mapa(bars + 8 * B_VX, w));
                __syncwarp();
            }
            if (lim == 0 && w == 3) {
                if (l16 == sb) bulk_s2g(g_qkv + (s * NH + head) * QKV_ITEM + RANK * 2560, sb + (ISV ? R_VT + (vto == 0 ? 20480 : vto - 10240) : R_QK + 10240 - vto), 10240);
                __syncwarp();
            }
            uint32_t bad = 0;
#pragma unroll
            for (int i = 0; i < 3; i++) {
                bad |= (odd ? a[2 * i].w : a[2 * i + 1].w) ^ 0x42004200u;
                const uint32_t mg = odd ? a[2 * i + 1].w : a[2 * i].w;
                stsm4(st1 + i * 896, a[2 * i].x, a[2 * i].y, a[2 * i].z, mg);
                stsm4(st2 + i * 896, a[2 * i + 1].x, a[2 * i + 1].y, a[2 * i + 1].z, mg);
            }
            if (__all_sync(~0u, bad == 0)) break;
            if (++lim > (1 << 20)) __trap();
        }
        TS(5);
    }
#undef LANE
#undef TSW
#define TSW warp
#undef first
}

#define KEEP12(x) asm volatile("" : "+f"(x[0]), "+f"(x[1]), "+f"(x[2]), "+f"(x[3]), "+f"(x[4]), "+f"(x[5]), "+f"(x[6]), "+f"(x[7]), \
                                    "+f"(x[8]), "+f"(x[9]), "+f"(x[10]), "+f"(x[11])::"memory")
#define KEEP16(x) asm volatile("" : "+f"(x[0]), "+f"(x[1]), "+f"(x[2]), "+f"(x[3]), "+f"(x[4]), "+f"(x[5]), "+f"(x[6]), "+f"(x[7]), \
                                    "+f"(x[8]), "+f"(x[9]), "+f"(x[10]), "+f"(x[11]), "+f"(x[12]), "+f"(x[13]), "+f"(x[14]), "+f"(x[15])::"memory")

template <int RANK>
__device__ __forceinline__ void main_loop(const uint32_t sb, const int head, const int warp, const uint32_t (&wk_)[20][4], const uint32_t (&ws_)[20][4], const CUtensorMap* tmX, const int poll_delay) {
    const uint32_t bars = sb + R_BAR;
    constexpr bool ISV = RANK == 2;
    constexpr int rank = RANK;
    const int j = warp >> 2, w = warp & 3;
    uint32_t l16 = pin(sb + (threadIdx.x & 31) * 16);
    uint32_t cst, wo0, wo1;
    const uint4* rp;
    {
        const int lane = threadIdx.x & 31, m = lane >> 3, r8 = lane & 7;
        const int isk = (lane >> 4) ^ j, hi = (lane >> 3) & 1;
        cst = pin(sb + w * 512 + r8 * 16 + (isk ? R_QK + 8192 + j * 256 + hi * 128 : R_QS + j * 128 + hi * 256));
        const int gb = (warp >> 1) * 7 + (warp & 1) * 3;
        const int G0 = gb + (m & 1);
        const int G1 = (m & 1) ? (warp >> 1) * 7 + 6 : gb + 2;
        const uint32_t rowo = sb + R_WO + ((m >> 1) * 8 + r8) * 128;
        wo0 = pin(rowo + (G0 >> 3) * 16384 + (((G0 & 7) ^ r8) << 4));
        wo1 = pin(rowo + (G1 >> 3) * 16384 + (((G1 & 7) ^ r8) << 4));
        rp = g_acc + pin(((rank * 8 + warp) * 4 + m) * ACC_LINE + (lane & 3) * 2 + ((lane >> 2) & 1));
    }

    auto xdesc = [&](int t) { return mkdesc(sb + R_XB + (t & 1) * 40960 + j * 20480, 16, 1024) | (1ull << 62); };
    auto put_partial = [&](float* xs) {
        const uint32_t ex = l16 + R_EX + warp * 1024;
        sts128(ex, pack2(xs[0], xs[1]), pack2(xs[2], xs[3]), pack2(xs[4], xs[5]), pack2(xs[6], xs[7]));
        sts128(ex + 512, pack2(xs[8], xs[9]), pack2(xs[10], xs[11]), pack2(xs[12], xs[13]), pack2(xs[14], xs[15]));
    };
    uint32_t f0[5][4], f1[5][4];
    uint32_t vto = 0;
    auto vproject = [&](int t) {
        float xk[16];
        const uint64_t d1 = mkdesc(sb + R_XB + (t & 1) * 40960, 16, 1024) | (1ull << 62);
        if (t < NSEG) mbar_wait(bars + 8 * (B_X0 + (t & 1)), (t >> 1) & 1);
        WG_FENCE();
#pragma unroll
        for (int k = 0; k < 40; k++) {
            const uint64_t dk = d1 + (uint64_t)(((k >> 2) * 4096 + (k & 3) * 32) >> 4);
            if (k == 0) wgmma_n32_rs_z(xk, wk_[0], dk); else wgmma_n32_rs<1>(xk, k < 20 ? wk_[k % 20] : ws_[k % 20], dk);
            if (k == 4) { ldsm4t(f0[0], wo0); ldsm4t(f1[0], wo1); ldsm4t(f0[1], wo0 + 4 * 2048); ldsm4t(f1[1], wo1 + 4 * 2048); }
        }
        WG_COMMIT();
        const uint32_t dst = l16 + R_VT + vto + warp * 1024;
        vto = vto == 20480 ? 0 : vto + 10240;
        WG_WAIT0();
        KEEP16(xk);
        stsm4(dst, pack2(xk[0], xk[1]), pack2(xk[4], xk[5]), pack2(xk[8], xk[9]), pack2(xk[12], xk[13]));
        stsm4(dst + 512, pack2(xk[2], xk[3]), pack2(xk[6], xk[7]), pack2(xk[10], xk[11]), pack2(xk[14], xk[15]));
    };
    auto window = [&](int t) {
        if (ISV) { vproject(t + 1); return; }
        float xs[16], xk[16];
        uint32_t o[8], pk[8];
        lds128(o, l16 + R_EX + (warp ^ 4) * 1024); lds128(o + 4, l16 + R_EX + (warp ^ 4) * 1024 + 512);
        const uint64_t d1 = xdesc(t), d2 = xdesc(t + 1);
        WG_FENCE();
#pragma unroll
        for (int k = 0; k < GK1; k++) {
            const uint64_t dk = d1 + (uint64_t)(((k >> 2) * 4096 + (k & 3) * 32) >> 4);
            if (k == 0) wgmma_n32_rs_z(xk, wk_[k], dk); else wgmma_n32_rs<1>(xk, wk_[k], dk);
        }
        WG_COMMIT();
        if (t + 1 < NSEG) mbar_wait(bars + 8 * (B_X0 + ((t + 1) & 1)), ((t + 1) >> 1) & 1);
#pragma unroll
        for (int k = 0; k < GK2; k++) {
            const uint64_t dk = d2 + (uint64_t)(((k >> 2) * 4096 + (k & 3) * 32) >> 4);
            if (k == 0) wgmma_n32_rs_z(xs, ws_[k], dk); else wgmma_n32_rs<1>(xs, ws_[k], dk);
        }
        WG_COMMIT();
        asm volatile("wgmma.wait_group.sync.aligned 1;" ::: "memory");
        KEEP16(xk);
#pragma unroll
        for (int i = 0; i < 8; i++) pk[i] = pack2(xk[2 * i] + __uint_as_float(o[i] << 16), xk[2 * i + 1] + __uint_as_float(o[i] & 0xFFFF0000u));
        bar_arrive_r(NB_EX + j, 256);
        {
            const uint32_t dst = l16 + R_QK + (t & 1) * 10240 + warp * 1024;
            stsm4(dst, pk[0], pk[1], pk[2], pk[3]); stsm4(dst + 512, pk[4], pk[5], pk[6], pk[7]);
        }
#pragma unroll
        for (int k = 8; k < GK3; k++) {
            const uint64_t dk = d2 + (uint64_t)(((k >> 2) * 4096 + (k & 3) * 32) >> 4);
            wgmma_n32_rs<1>(xs, ws_[k], dk);
        }
        WG_COMMIT();
        bar_sync_r(NB_EX + 1 - j, 256);
        WG_WAIT0();
        KEEP16(xs);
        put_partial(xs);
    };
    if (ISV) {
        vproject(0);
        fence_proxy_async();
        bar_arrive<NB_QK, 384>();
        mbar_wait(bars + 8 * B_WO, 0);
    } else {
        float xs[16];
        const uint64_t d2 = xdesc(0);
        mbar_wait(bars + 8 * B_X0, 0);
        WG_FENCE();
#pragma unroll
        for (int k = 0; k < 20; k++) {
            const uint64_t dk = d2 + (uint64_t)(((k >> 2) * 4096 + (k & 3) * 32) >> 4);
            if (k == 0) wgmma_n32_rs_z(xs, ws_[k], dk); else wgmma_n32_rs<1>(xs, ws_[k], dk);
        }
        WG_COMMIT();
        WG_WAIT0();
        KEEP16(xs);
        put_partial(xs);
        mbar_wait(bars + 8 * (B_X0 + 1), 0);
        mbar_wait(bars + 8 * B_WO, 0);
        bar_sync<NB_EPI, 256>();
    }
#pragma unroll 1
    for (int s = -1;;) {
        window(s + 1);
        TS(4);
        s++;
        LOCAL();
        bar_sync<NB_MEM, 384>();
        {
            float ca[2][4], cb[2][4];
#pragma unroll
            for (int i = 0; i < 10; i++) {
                uint32_t b[4], b2[4];
                ldsm4t(b, l16 + R_MEM + (ISV ? 0 : j * 5120) + i * 512);
                if (ISV) ldsm4t(b2, l16 + R_MEM + 5120 + i * 512);
                const uint32_t* bs = ISV ? b2 : b;
                if (i == 1) TS(0);
                if (!ISV) {
                    if (i == 3) ldsm4t(f0[0], wo0);
                    if (i == 5) ldsm4t(f1[0], wo1);
                    if (i == 7) ldsm4t(f0[1], wo0 + 4 * 2048);
                    if (i == 9) ldsm4t(f1[1], wo1 + 4 * 2048);
                }
                if (i == 0) {
                    mma16816z(ca[0], wk_[0], b[0], b[1]); mma16816z(cb[0], ws_[0], bs[0], bs[1]);
                    mma16816z(ca[1], wk_[1], b[2], b[3]); mma16816z(cb[1], ws_[1], bs[2], bs[3]);
                } else {
                    mma16816(ca[0], wk_[2 * i], b[0], b[1]); mma16816(cb[0], ws_[2 * i], bs[0], bs[1]);
                    mma16816(ca[1], wk_[2 * i + 1], b[2], b[3]); mma16816(cb[1], ws_[2 * i + 1], bs[2], bs[3]);
                }
            }
#pragma unroll
            for (int e = 0; e < 4; e++) { ca[0][e] += ca[1][e]; cb[0][e] += cb[1][e]; }
            if (!ISV) {
                stsm4(cst, pack2(ca[0][0], ca[0][1]), pack2(ca[0][2], ca[0][3]), pack2(cb[0][0], cb[0][1]), pack2(cb[0][2], cb[0][3]));
                if (s < NSEG - 1) bar_arrive<NB_QK, 352>();
                if (cst < sb + R_QS) cst += (s & 1) ? -10240 : 10240;
            } else {
                const uint32_t row = (l16 & ~0x100u) + warp * 256 + R_VT + 8192;
                const uint32_t loc = row + (vto == 20480 ? 0 : vto + 10240);
                asm volatile("stmatrix.sync.aligned.m8n8.x2.shared.b16 [%0], {%1,%2};" ::"r"(loc), "r"(pack2(ca[0][0] + cb[0][0], ca[0][1] + cb[0][1])),
                             "r"(pack2(ca[0][2] + cb[0][2], ca[0][3] + cb[0][3])) : "memory");
                if (s < NSEG - 1) {
                    uint32_t r[4];
                    __syncwarp();
                    lds128(r, loc);
                    const uint32_t peer = (l16 >> 8) & 1;
                    st_async4(mapa(row + (s & 1) * 10240, peer), r[0], r[1], r[2], r[3], mapa(bars + 8 * B_V, peer));
                    bar_arrive<NB_QK, 384>();
                }
            }
            TS(1);
            fence_proxy_async();
        }
        if (s == NSEG - 1) break;
        {
            if (!ISV) bar_sync<NB_SENT, 352>();
            ldsm4t(f0[2], wo0 + 1 * 2048); ldsm4t(f1[2], wo1 + 1 * 2048);
            ldsm4t(f0[3], wo0 + 5 * 2048); ldsm4t(f1[3], wo1 + 5 * 2048);
            ldsm4t(f0[4], wo0 + 2 * 2048); ldsm4t(f1[4], wo1 + 2 * 2048);
            if (warp == 0 && s + 2 < NSEG) {
                mbar_wait_cl(bars + 8 * B_S, s & 1);
                if (!ISV) mbar_wait_cl(bars + 8 * B_V, s & 1);
                if (l16 == sb) xload(sb, tmX, s, RANK, head);
                __syncwarp();
            }
            bar_sync<NB_O, 384>();
            float d0[4], d1[4];
            uint32_t b0[4], b1[4], b2[4];
            ldsm4t(b0, l16 + R_OB); ldsm4t(b1, l16 + R_OB + 512);
            SCHED_FENCE();
            TS(2);
            mma16816z(d0, f0[0], b0[0], b0[1]); mma16816z(d1, f1[0], b0[0], b0[1]);
            ldsm4t(b2, l16 + R_OB + 1024);
            mma16816(d0, f0[1], b0[2], b0[3]); mma16816(d1, f1[1], b0[2], b0[3]);
            ldsm4t(f0[1], wo0 + 6 * 2048); ldsm4t(f1[1], wo1 + 6 * 2048); ldsm4t(b0, l16 + R_OB + 1536);
            mma16816(d0, f0[2], b1[0], b1[1]); mma16816(d1, f1[2], b1[0], b1[1]);
            ldsm4t(f0[2], wo0 + 3 * 2048); ldsm4t(f1[2], wo1 + 3 * 2048);
            mma16816(d0, f0[3], b1[2], b1[3]); mma16816(d1, f1[3], b1[2], b1[3]);
            ldsm4t(f0[3], wo0 + 7 * 2048); ldsm4t(f1[3], wo1 + 7 * 2048);
            float sm[2];
            lds64f(sm, l16 + R_SUM);
            mma16816(d0, f0[4], b2[0], b2[1]); mma16816(d1, f1[4], b2[0], b2[1]);
            mma16816(d0, f0[1], b2[2], b2[3]); mma16816(d1, f1[1], b2[2], b2[3]);
            mma16816(d0, f0[2], b0[0], b0[1]); mma16816(d1, f1[2], b0[0], b0[1]);
            mma16816(d0, f0[3], b0[2], b0[3]); mma16816(d1, f1[3], b0[2], b0[3]);
            const float r0 = rcp(sm[0]), r1 = rcp(sm[1]);
            const uint32_t w3 = (((l16 >> 6) ^ warp) & 1) ? 0x3F803F80u : pack2(d1[2] * r0, d1[3] * r1);
            asm volatile("red.relaxed.gpu.global.add.noftz.v4.bf16x2 [%0], {%1,%2,%3,%4};"
                         ::"l"(rp), "r"(pack2(d0[0] * r0, d0[1] * r1)), "r"(pack2(d0[2] * r0, d0[3] * r1)), "r"(pack2(d1[0] * r0, d1[1] * r1)), "r"(w3) : "memory");
            TS(3);
            bar_sync<NB_EPI, 256>();
        }
        rp += (s & 15) == 15 ? -15 * ACC_SLOT : ACC_SLOT;
    }
    bar_sync<NB_EPI, 256>();
    if (threadIdx.x == 160) {
        bulk_s2g(g_qkv + ((NSEG - 1) * NH + head) * QKV_ITEM + RANK * 2560, sb + (ISV ? R_VT + (NSEG - 1) % 3 * 10240 : R_QK + 10240), 10240);
        asm volatile("cp.async.bulk.wait_group 0;\n\tfence.proxy.async.global;" ::: "memory");
        fence_release_gpu();
        red_add_gpu(&g_qready[NSEG - 1]);
    }
    __syncwarp();
}

__global__ void __launch_bounds__(384, 1)
rec_kernel(const __grid_constant__ CUtensorMap tmX, const __grid_constant__ CUtensorMap tmWq, const __grid_constant__ CUtensorMap tmWk,
           const __grid_constant__ CUtensorMap tmWv, const __grid_constant__ CUtensorMap tmWo, const bf16* __restrict__ mem0, const int poll_delay) {
    extern __shared__ uint8_t smem_raw[];
    const uint32_t sb = (smem_u32(smem_raw) + 1023) & ~1023u;
    uint32_t rank; asm volatile("mov.u32 %0, %%cluster_ctarank;" : "=r"(rank));
    const int head = blockIdx.x / 3;
    const uint32_t bars = sb + R_BAR;

    if (threadIdx.x == 0) {
        for (int i = 0; i < B_NUM; i++) mbar_init(bars + 8 * i, i == B_XF ? 12 : (i == B_S && rank < 2) ? 4 : 1);
        asm volatile("fence.mbarrier_init.release.cluster;" ::: "memory");
        fence_proxy_async();
        const CUtensorMap* mA = rank == 2 ? &tmWv : &tmWq;
        const CUtensorMap* mB = rank == 2 ? &tmWv : &tmWk;
        const int colA = head * 128 + (rank == 1 ? 64 : 0), colB = head * 128 + (rank == 0 ? 0 : 64);
        for (int q = 0; q < 4; q++) {
            mbar_expect(bars + 8 * (B_W0 + q), 40960);
            tma2d(sb + R_WST + q * 20480, mA, colA, q * 160, bars + 8 * (B_W0 + q));
            tma2d(sb + R_WST + (4 + q) * 20480, mB, colB, q * 160, bars + 8 * (B_W0 + q));
        }
        mbar_expect(bars + 8 * (B_X0 + 0), 40960);
        mbar_expect(bars + 8 * (B_X0 + 1), 40960);
    }
    asm volatile("griddepcontrol.launch_dependents;" ::: "memory");
    __syncthreads();
    cluster_sync_relaxed();
    if (threadIdx.x == 0) {
        if (rank < 2) tma3d_mc(sb + R_XB + rank * 20480, &tmX, 0, rank * 5, bars + 8 * B_X0, 7);
        for (int q = 0; q < 4; q++) tma2d_prefetch(&tmWo, rank * 224 + q * 64, head * 128);
    }
    __syncwarp();

    if (threadIdx.x < 256) {
        asm volatile("setmaxnreg.inc.sync.aligned.u32 224;");
        const int warp = __shfl_sync(~0u, threadIdx.x >> 5, 0), j = warp >> 2;
        uint32_t wk_[20][4], ws_[20][4];
        {
            const int lane = threadIdx.x & 31, w = warp & 3, m = lane >> 3, r8 = lane & 7;
            const uint32_t la = ((m >> 1) * 8 + r8) * 128 + (((2 * w + (m & 1)) ^ r8) << 4);
#pragma unroll
            for (int hlf = 0; hlf < 2; hlf++) {
                const int qk = rank == 2 ? hlf : 2 * j + hlf, qs = rank == 2 ? 2 + hlf : 2 * j + hlf;
                mbar_wait(bars + 8 * (B_W0 + qk), 0);
                mbar_wait(bars + 8 * (B_W0 + qs), 0);
                const uint32_t bk = sb + R_WST + (j * 4 + qk) * 20480 + la, bs = sb + R_WST + ((rank == 2 ? j : 1 - j) * 4 + qs) * 20480 + la;
#pragma unroll
                for (int k = 0; k < 10; k++) {
                    ldsm4t(wk_[hlf * 10 + k], bk + k * 2048);
                    ldsm4t(ws_[hlf * 10 + k], bs + k * 2048);
                }
            }
        }
        fence_proxy_async();
        cluster_sync_all();
        if (threadIdx.x == 0) {
            if (rank < 2) tma3d_mc(sb + R_XB + 40960 + rank * 20480, &tmX, SEG, rank * 5, bars + 8 * (B_X0 + 1), 7);
            mbar_expect(bars + 8 * B_WO, 65536);
            for (int q = 0; q < 4; q++) tma2d(sb + R_WO + q * 16384, &tmWo, rank * 224 + q * 64, head * 128, bars + 8 * B_WO);
        }
        __syncwarp();
        if (rank == 0) main_loop<0>(sb, head, warp, wk_, ws_, &tmX, poll_delay);
        else if (rank == 1) main_loop<1>(sb, head, warp, wk_, ws_, &tmX, poll_delay);
        else main_loop<2>(sb, head, warp, wk_, ws_, &tmX, poll_delay);
        cluster_sync_all();
    } else {
        asm volatile("setmaxnreg.dec.sync.aligned.u32 56;");
        if (threadIdx.x < 256 + 64) {
            g_acc[((threadIdx.x - 256) >> 3) * ACC_SLOT + blockIdx.x * ACC_LINE + (threadIdx.x & 7)] = make_uint4(0, 0, 0, 0);
            fence_release_gpu();
            __syncwarp();
            if ((threadIdx.x & 31) == 0) red_add_gpu(&g_start);
        }
        cluster_sync_all();
        for (int i = threadIdx.x - 256; i < DM * 4; i += 128) {
            const int col = i >> 2, rp = i & 3;
            const uint32_t lo = __bfloat16_as_ushort(mem0[(2 * rp) * DM + col]), hi = __bfloat16_as_ushort(mem0[(2 * rp + 1) * DM + col]);
            asm volatile("st.shared.u32 [%0], %1;" ::"r"(sb + R_MEM + i * 4), "r"(lo | (hi << 16)) : "memory");
        }
        if (threadIdx.x == 256) {
            unsigned v; int lim = 0;
            do { asm volatile("ld.acquire.gpu.global.u32 %0, [%1];" : "=r"(v) : "l"(&g_start) : "memory"); if (++lim > (1 << 22)) __trap(); } while (v < 192);
        }
        __syncwarp();
        if (rank == 0) aux_loop<0>(sb, head, &tmX, poll_delay);
        else if (rank == 1) aux_loop<1>(sb, head, &tmX, poll_delay);
        else aux_loop<2>(sb, head, &tmX, poll_delay);
        __syncwarp();
        cluster_sync_all();
    }
}

constexpr int G_STAGES = 6, G_STAGE = 32768;
constexpr int G_BAR = G_STAGES * G_STAGE;
constexpr int G_SMEM = G_BAR + 256 + 1024;
enum { T_EXIT = 0, T_H = 1, T_F = 2, T_A = 3, T_GATE = 4 };
enum { C_QA = 0, C_QO = 32, C_QP = 64, C_QH = 96, C_DONE = 128, C_HREADY = 160, C_OREADY = 192, C_PDONE = 224, C_FCNT = 320, C_NUM = 416 };
__device__ unsigned g_cnt[C_NUM];
__device__ float g_gate[S_TOK];
__device__ __align__(1024) float4 g_ws[80 * 4096];
constexpr int N_QA = 256, N_QP = 80, N_QH = 16 + 16 * KC_H;
constexpr int N_QO = 5 * (12 + 2 + 2 + 4 + 16);

__device__ __forceinline__ unsigned ld_relaxed(const unsigned* p) { unsigned v; asm volatile("ld.relaxed.gpu.global.u32 %0, [%1];" : "=r"(v) : "l"(p) : "memory"); return v; }
__device__ __forceinline__ void bulk_g2s(uint32_t dst, const void* src, int bytes, uint32_t bar) {
    asm volatile("cp.async.bulk.shared::cluster.global.mbarrier::complete_tx::bytes [%0], [%1], %2, [%3];" ::"r"(dst), "l"(src), "r"(bytes), "r"(bar) : "memory");
}
__device__ __forceinline__ void mbar_wait1(uint32_t b, int par) {
    uint32_t ok; int lim = 0;
    while (true) {
        asm volatile("{.reg .pred p; mbarrier.try_wait.parity.shared::cta.b64 p, [%1], %2; selp.u32 %0, 1, 0, p;}" : "=r"(ok) : "r"(b), "r"(par) : "memory");
        if (ok) break;
        if (++lim > (1 << 22)) __trap();
    }
}
__device__ __forceinline__ void wgmma_n128(float* d, uint64_t da, uint64_t db, int acc) {
    asm volatile("{\n\t.reg .pred p;\n\tsetp.ne.s32 p, %66, 0;\n\t"
                 "wgmma.mma_async.sync.aligned.m64n128k16.f32.bf16.bf16 {%0,%1,%2,%3,%4,%5,%6,%7,%8,%9,%10,%11,%12,%13,%14,%15,%16,%17,%18,%19,%20,%21,%22,%23,%24,%25,%26,%27,%28,%29,%30,%31,"
                 "%32,%33,%34,%35,%36,%37,%38,%39,%40,%41,%42,%43,%44,%45,%46,%47,%48,%49,%50,%51,%52,%53,%54,%55,%56,%57,%58,%59,%60,%61,%62,%63}, %64, %65, p, 1, 1, 0, 1;\n\t}"
                 : "+f"(d[0]), "+f"(d[1]), "+f"(d[2]), "+f"(d[3]), "+f"(d[4]), "+f"(d[5]), "+f"(d[6]), "+f"(d[7]), "+f"(d[8]), "+f"(d[9]), "+f"(d[10]), "+f"(d[11]),
                   "+f"(d[12]), "+f"(d[13]), "+f"(d[14]), "+f"(d[15]), "+f"(d[16]), "+f"(d[17]), "+f"(d[18]), "+f"(d[19]), "+f"(d[20]), "+f"(d[21]), "+f"(d[22]), "+f"(d[23]),
                   "+f"(d[24]), "+f"(d[25]), "+f"(d[26]), "+f"(d[27]), "+f"(d[28]), "+f"(d[29]), "+f"(d[30]), "+f"(d[31]), "+f"(d[32]), "+f"(d[33]), "+f"(d[34]), "+f"(d[35]),
                   "+f"(d[36]), "+f"(d[37]), "+f"(d[38]), "+f"(d[39]), "+f"(d[40]), "+f"(d[41]), "+f"(d[42]), "+f"(d[43]), "+f"(d[44]), "+f"(d[45]), "+f"(d[46]), "+f"(d[47]),
                   "+f"(d[48]), "+f"(d[49]), "+f"(d[50]), "+f"(d[51]), "+f"(d[52]), "+f"(d[53]), "+f"(d[54]), "+f"(d[55]), "+f"(d[56]), "+f"(d[57]), "+f"(d[58]), "+f"(d[59]),
                   "+f"(d[60]), "+f"(d[61]), "+f"(d[62]), "+f"(d[63])
                 : "l"(da), "l"(db), "r"(acc));
}
__device__ __forceinline__ void decode_qo(int i, int& tb, int& nt, int& lg, int& sp) {
    int r;
    if (i < 60) { tb = i / 5; r = i - tb * 5; lg = 0; }
    else if (i < 80) { tb = 12 + (i - 60) / 10; r = (i - 60) % 10; lg = 1; }
    else if (i < 100) { tb = 14; r = i - 80; lg = 2; }
    else { tb = 15; r = i - 100; lg = 4; }
    nt = r % 5; sp = r / 5;
}

__global__ void __launch_bounds__(288, 1)
gemm_kernel(const __grid_constant__ CUtensorMap tmX, const __grid_constant__ CUtensorMap tmWg, const __grid_constant__ CUtensorMap tmWu,
            const __grid_constant__ CUtensorMap tmWo, const __grid_constant__ CUtensorMap tmWd, const bf16* __restrict__ x, const bf16* __restrict__ gw,
            bf16* __restrict__ out) {
    extern __shared__ uint8_t smem_raw[];
    const uint32_t sb = (smem_u32(smem_raw) + 1023) & ~1023u;
    const uint32_t full = sb + G_BAR, empty = full + 48, info = full + 96, sflag = full + 128;
    const int tid = threadIdx.x, warp = __shfl_sync(~0u, tid >> 5, 0), lane = tid & 31;
    if (tid == 0) {
        for (int i = 0; i < G_STAGES; i++) { mbar_init(full + 8 * i, 1); mbar_init(empty + 8 * i, 2); }
        fence_proxy_async();
    }
    __syncthreads();

    if (warp == 8) {
        if (lane == 0) {
            int st = 0, ph = 1, idle = 0, pa = -1, po = -1, pp = -1;
            auto availA = [&](int i) { const int seg = i >> 2; return ld_relaxed(g_qready + (seg >= NSEG - 4 ? seg : (seg | 3))) == 96; };
            auto availO = [&](int i) { int tb, nt, lg, sp; decode_qo(i, tb, nt, lg, sp); return (ld_relaxed(g_cnt + C_OREADY + tb) == 16) & (ld_relaxed(g_cnt + C_PDONE + tb * 5 + nt) != 0); };
            auto availP = [&](int i) { return ld_relaxed(g_cnt + C_HREADY + i / 5) == KC_H + 1; };
            auto next = [&]() { if (++st == G_STAGES) { st = 0; ph ^= 1; } };
            while (true) {
                int task = -1;
                const unsigned qa = pa >= 0 ? pa : ld_relaxed(g_cnt + C_QA), qo = po >= 0 ? po : ld_relaxed(g_cnt + C_QO);
                const unsigned qp = pp >= 0 ? pp : ld_relaxed(g_cnt + C_QP), qh = ld_relaxed(g_cnt + C_QH);
                const bool va = qa < N_QA && availA(qa), vo = qo < N_QO && availO(qo), vp = qp < N_QP && availP(qp);
                const bool owing = (pa >= 0 && pa < N_QA) || (po >= 0 && po < N_QO) || (pp >= 0 && pp < N_QP);
                if (va) {
                    if (pa < 0) { pa = atomicAdd(g_cnt + C_QA, 1); if (pa != qa && !(pa < N_QA && availA(pa))) continue; }
                    task = T_A | (pa << 3); pa = -1;
                } else if (vo && (po >= 0 || !owing)) {
                    if (po < 0) { po = atomicAdd(g_cnt + C_QO, 1); if (po != qo && !(po < N_QO && availO(po))) continue; }
                    int tb, nt, lg, sp; decode_qo(po, tb, nt, lg, sp);
                    task = T_F | (tb << 3) | (nt << 7) | ((sp * (64 >> lg)) << 10) | ((64 >> lg) << 17) | ((lg + 1) << 24); po = -1;
                } else if (vp && (pp >= 0 || !(pa >= 0 && pa < N_QA))) {
                    if (pp < 0) { pp = atomicAdd(g_cnt + C_QP, 1); if (pp != qp && !(pp < N_QP && availP(pp))) continue; }
                    task = T_F | ((pp / 5) << 3) | ((pp % 5) << 7) | (KC_O << 10) | (KC_H << 17); pp = -1;
                } else if (qh < N_QH) {
                    const unsigned i = atomicAdd(g_cnt + C_QH, 1);
                    if (i >= N_QH) continue;
                    task = i < 16 ? T_GATE | (i << 3) : T_H | (((i - 16) / KC_H) << 3) | (((i - 16) % KC_H) << 7);
                } else if (qa >= N_QA && qo >= N_QO && qp >= N_QP) {
                    task = T_EXIT;
                } else {
                    __nanosleep(100);
                    if (++idle > (1 << 22)) __trap();
                    continue;
                }
                asm volatile("fence.acq_rel.gpu;\n\tfence.proxy.async.global;" ::: "memory");
                const int type = task & 7, tb = (task >> 3) & 15;
                mbar_wait1(empty + 8 * st, ph);
                asm volatile("st.shared.u32 [%0], %1;" ::"r"(info + 4 * st), "r"(task) : "memory");
                if (type == T_EXIT || type == T_GATE) {
                    mbar_arrive(full + 8 * st); next();
                    if (type == T_EXIT) break;
                } else if (type == T_H) {
                    const int cb = task >> 7;
                    for (int k = 0; k < 10; k++) {
                        if (k) mbar_wait1(empty + 8 * st, ph);
                        const uint32_t d = sb + st * G_STAGE, b = full + 8 * st;
                        mbar_expect(b, 32768);
                        tma2d(d, &tmX, k * 64, tb * 128, b);
                        tma2d(d + 16384, &tmWg, cb * 64, k * 64, b);
                        tma2d(d + 24576, &tmWu, cb * 64, k * 64, b);
                        next();
                    }
                } else if (type == T_F) {
                    const int nt = (task >> 7) & 7, k0 = (task >> 10) & 127, nk = (task >> 17) & 127;
                    const CUtensorMap* mw = k0 >= KC_O ? &tmWd : &tmWo;
                    for (int k = k0; k < k0 + nk; k++) {
                        if (k > k0) mbar_wait1(empty + 8 * st, ph);
                        const uint32_t d = sb + st * G_STAGE, b = full + 8 * st;
                        const int row = (k >= KC_O ? k - KC_O : k) * 64;
                        mbar_expect(b, 32768);
                        bulk_g2s(d, g_act + (tb * KC_ALL + k) * 4096, 16384, b);
                        tma2d(d + 16384, mw, nt * 128, row, b);
                        tma2d(d + 24576, mw, nt * 128 + 64, row, b);
                        next();
                    }
                } else {
                    const int item0 = (task >> 3) * 8;
                    for (int k = 0; k < 8; k++) {
                        if (k) mbar_wait1(empty + 8 * st, ph);
                        mbar_expect(full + 8 * st, QKV_ITEM * 4);
                        bulk_g2s(sb + st * G_STAGE, g_qkv + (size_t)(item0 + k) * QKV_ITEM, QKV_ITEM * 4, full + 8 * st);
                        next();
                    }
                }
            }
        }
    } else {
        const int wg = warp >> 2, g = lane >> 2, c = lane & 3;
        int st = 0, ph = 0;
        auto next = [&]() { if (++st == G_STAGES) { st = 0; ph ^= 1; } };
        while (true) {
            mbar_wait(full + 8 * st, ph);
            int task; asm volatile("ld.shared.u32 %0, [%1];" : "=r"(task) : "r"(info + 4 * st) : "memory");
            task = __shfl_sync(~0u, task, 0);
            const int type = task & 7, tb = (task >> 3) & 15;
            if (type == T_EXIT) break;
            unsigned* done_ctr;
            if (type == T_GATE) {
                bar_sync<1, 256>();
                if ((tid & 127) == 0) mbar_arrive(empty + 8 * st);
                next();
                float wv[20];
#pragma unroll
                for (int i = 0; i < 10; i++) { const uint32_t u = ((const uint32_t*)gw)[i * 32 + lane]; wv[2 * i] = __uint_as_float(u << 16); wv[2 * i + 1] = __uint_as_float(u & 0xFFFF0000u); }
#pragma unroll 4
                for (int r = 0; r < 16; r++) {
                    const int row = tb * 128 + warp * 16 + r;
                    float a = 0.f;
#pragma unroll
                    for (int i = 0; i < 10; i++) {
                        const uint32_t u = ((const uint32_t*)x)[row * (DM / 2) + i * 32 + lane];
                        a = fmaf(__uint_as_float(u << 16), wv[2 * i], a); a = fmaf(__uint_as_float(u & 0xFFFF0000u), wv[2 * i + 1], a);
                    }
#pragma unroll
                    for (int o = 16; o; o >>= 1) a += __shfl_xor_sync(~0u, a, o);
                    if (lane == 0) g_gate[row] = 1.f / (1.f + __expf(-a));
                }
                done_ctr = g_cnt + C_HREADY + tb;
            } else if (type == T_A) {
                mbar_wait(full + 8 * (st == G_STAGES - 1 ? 0 : st + 1), st == G_STAGES - 1 ? ph ^ 1 : ph);
                bar_sync<1, 256>();
                const int item0 = (task >> 3) * 8, m = warp & 1, mi = lane >> 3;
                const float SC = 0.08838834764831845f * 1.4426950408889634f;
#pragma unroll 1
                for (int k = 0; k < 8; k++) {
                    if ((k & 3) == (warp >> 1)) {
                        mbar_wait(full + 8 * st, ph);
                        const uint32_t base = sb + st * G_STAGE, l16 = base + lane * 16;
                        const uint32_t qa = base + (2 * m + (mi & 1)) * 256 + (mi >> 1) * 128 + (lane & 7) * 16;
                        float sv[5][4];
#pragma unroll
                        for (int i = 0; i < 5; i++)
#pragma unroll
                            for (int e = 0; e < 4; e++) sv[i][e] = 0.f;
#pragma unroll
                        for (int ks = 0; ks < 8; ks++) {
                            const int ho = (ks >> 2) * 10240, k4 = ks & 3;
                            uint32_t qf[4], k0[4], k1[4], km[4];
                            ldsm4t(qf, qa + ho + k4 * 1024); ldsm4t(k0, l16 + ho + 4096 + k4 * 1024); ldsm4t(km, l16 + ho + 8192 + k4 * 512);
                            mma16816(sv[0], qf, k0[0], k0[1]); mma16816(sv[1], qf, k0[2], k0[3]);
                            mma16816(sv[4], qf, km[0], km[1]);
                            if (m) { ldsm4t(k1, l16 + ho + 4096 + k4 * 1024 + 512); mma16816(sv[2], qf, k1[0], k1[1]); mma16816(sv[3], qf, k1[2], k1[3]); }
                            mma16816(sv[4], qf, km[2], km[3]);
                        }
#pragma unroll
                        for (int i = 0; i < 4; i++)
#pragma unroll
                            for (int e = 0; e < 4; e++)
                                if (8 * i + (e & 1) - (e >> 1) * 8 > 16 * m + g - 2 * c) sv[i][e] = -INFINITY;
                        float mx0 = fmaxf(sv[4][0], sv[4][1]), mx1 = fmaxf(sv[4][2], sv[4][3]);
#pragma unroll
                        for (int i = 0; i < 4; i++) { mx0 = fmaxf(mx0, fmaxf(sv[i][0], sv[i][1])); mx1 = fmaxf(mx1, fmaxf(sv[i][2], sv[i][3])); }
                        mx0 = fmaxf(mx0, __shfl_xor_sync(~0u, mx0, 1)); mx1 = fmaxf(mx1, __shfl_xor_sync(~0u, mx1, 1));
                        mx0 = fmaxf(mx0, __shfl_xor_sync(~0u, mx0, 2)); mx1 = fmaxf(mx1, __shfl_xor_sync(~0u, mx1, 2));
                        mx0 *= -SC; mx1 *= -SC;
                        float sum0 = 0.f, sum1 = 0.f;
#pragma unroll
                        for (int i = 0; i < 5; i++) {
                            sv[i][0] = ex2(fmaf(sv[i][0], SC, mx0)); sv[i][1] = ex2(fmaf(sv[i][1], SC, mx0));
                            sv[i][2] = ex2(fmaf(sv[i][2], SC, mx1)); sv[i][3] = ex2(fmaf(sv[i][3], SC, mx1));
                            sum0 += sv[i][0] + sv[i][1]; sum1 += sv[i][2] + sv[i][3];
                        }
                        sum0 += __shfl_xor_sync(~0u, sum0, 1); sum1 += __shfl_xor_sync(~0u, sum1, 1);
                        sum0 += __shfl_xor_sync(~0u, sum0, 2); sum1 += __shfl_xor_sync(~0u, sum1, 2);
                        const float r0 = rcp(sum0), r1 = rcp(sum1);
                        uint32_t pa[10];
#pragma unroll
                        for (int i = 0; i < 5; i++) { pa[2 * i] = pack2(sv[i][0] * r0, sv[i][1] * r0); pa[2 * i + 1] = pack2(sv[i][2] * r1, sv[i][3] * r1); }
                        const int item = item0 + k, seg = item >> 5, head = item & 31;
                        uint32_t* og = g_act + (((seg >> 2) * KC_ALL + 2 * head) * 16 + (seg & 3) * 4 + 2 * m) * 256 + lane;
#pragma unroll
                        for (int n4 = 0; n4 < 4; n4++) {
                            uint32_t vm[4];
                            ldsm4(vm, l16 + 28672 + n4 * 512);
#pragma unroll
                            for (int q = 0; q < 4; q++) {
                                const int n = n4 * 4 + q;
                                uint32_t vf[4];
                                float o[4];
                                ldsm4(vf, l16 + 20480 + n * 512);
                                mma1688z(o, pa[8], pa[9], vm[q]);
                                mma16816(o, pa, vf[0], vf[1]);
                                if (m) mma16816(o, pa + 4, vf[2], vf[3]);
                                og[(n >> 3) * 4096 + (n & 7) * 32] = pack2(o[0], o[1]);
                                og[(n >> 3) * 4096 + (n & 7) * 32 + 256] = pack2(o[2], o[3]);
                            }
                        }
                        __syncwarp();
                        if (lane == 0) mbar_arrive(empty + 8 * st);
                    }
                    next();
                }
                done_ctr = g_cnt + C_OREADY + (task >> 7);
            } else {
                const int nk = type == T_H ? 10 : (task >> 17) & 127;
                const uint64_t ahi = type == T_H ? ((1ull << 16) | (64ull << 32) | (1ull << 62)) : ((8ull << 16) | (64ull << 32));
                const uint32_t astep = type == T_H ? 2 : 16;
                const uint64_t bhi = (512ull << 16) | (64ull << 32) | (1ull << 62);
                float acc[64];
#pragma unroll
                for (int i = 0; i < 64; i++) acc[i] = 0.f;
                int pst = 0;
#pragma unroll 1
                for (int k = 0; k < nk; k++) {
                    if (k) mbar_wait(full + 8 * st, ph);
                    const uint32_t d = sb + st * G_STAGE;
                    const uint64_t da = ahi | (uint64_t)(((d + wg * 8192) & 0x3FFFF) >> 4), db = bhi | (uint64_t)(((d + 16384) & 0x3FFFF) >> 4);
                    WG_FENCE();
#pragma unroll
                    for (int q = 0; q < 4; q++) wgmma_n128(acc, da + q * astep, db + q * 128, k | q);
                    WG_COMMIT();
                    if (k) {
                        asm volatile("wgmma.wait_group.sync.aligned 1;" ::: "memory");
                        bar_sync_r(2 + wg, 128);
                        if ((tid & 127) == 0) mbar_arrive(empty + 8 * pst);
                    }
                    pst = st;
                    next();
                }
                WG_WAIT0();
                bar_sync_r(2 + wg, 128);
                if ((tid & 127) == 0) mbar_arrive(empty + 8 * pst);
                KEEP16(acc); KEEP16((acc + 16)); KEEP16((acc + 32)); KEEP16((acc + 48));
                if (type == T_H) {
                    uint32_t* hg = g_act + ((tb * KC_ALL + KC_O + (task >> 7)) * 16 + warp * 2) * 256 + lane;
#pragma unroll
                    for (int n = 0; n < 8; n++) {
                        hg[n * 32] = pack2(acc[4 * n] * acc[32 + 4 * n], acc[4 * n + 1] * acc[33 + 4 * n]);
                        hg[256 + n * 32] = pack2(acc[4 * n + 2] * acc[34 + 4 * n], acc[4 * n + 3] * acc[35 + 4 * n]);
                    }
                    done_ctr = g_cnt + C_HREADY + tb;
                } else {
                    const int nt = (task >> 7) & 7, mode = task >> 24, tile = tb * 5 + nt, row = tb * 128 + warp * 16 + g;
                    float g0 = __ldcg(g_gate + row), g1 = __ldcg(g_gate + row + 8);
                    float4* ws = g_ws + tile * 4096 + tid;
                    done_ctr = nullptr;
                    bool fin = mode == 1;
                    if (mode == 0) {
                        g0 = 1.f - g0; g1 = 1.f - g1;
#pragma unroll
                        for (int n = 0; n < 16; n++) __stcg(ws + n * 256, make_float4(acc[4 * n] * g0, acc[4 * n + 1] * g0, acc[4 * n + 2] * g1, acc[4 * n + 3] * g1));
                        done_ctr = g_cnt + C_PDONE + tile;
                    } else if (mode > 1) {
#pragma unroll
                        for (int n = 0; n < 16; n++)
                            asm volatile("red.relaxed.gpu.global.add.v4.f32 [%0], {%1,%2,%3,%4};" ::"l"(ws + n * 256), "f"(acc[4 * n] * g0), "f"(acc[4 * n + 1] * g0),
                                         "f"(acc[4 * n + 2] * g1), "f"(acc[4 * n + 3] * g1) : "memory");
                        __threadfence();
                        bar_sync<1, 256>();
                        if (tid == 0) {
                            const unsigned n = atomicAdd(g_cnt + C_FCNT + tile, 1);
                            __threadfence();
                            asm volatile("st.shared.u32 [%0], %1;" ::"r"(sflag), "r"(n) : "memory");
                        }
                        bar_sync<1, 256>();
                        unsigned n; asm volatile("ld.shared.u32 %0, [%1];" : "=r"(n) : "r"(sflag) : "memory");
                        fin = n == (1u << (mode - 1)) - 1;
                        g0 = 0.f; g1 = 0.f;
#pragma unroll
                        for (int i = 0; i < 64; i++) acc[i] = 0.f;
                    }
                    if (fin) {
                        uint32_t* og = (uint32_t*)out + row * (DM / 2) + nt * 64 + c;
#pragma unroll
                        for (int n = 0; n < 16; n++) {
                            const float4 v = __ldcg(ws + n * 256);
                            og[n * 4] = pack2(fmaf(acc[4 * n], g0, v.x), fmaf(acc[4 * n + 1], g0, v.y));
                            og[n * 4 + 8 * (DM / 2)] = pack2(fmaf(acc[4 * n + 2], g1, v.z), fmaf(acc[4 * n + 3], g1, v.w));
                        }
                    }
                }
            }
            if (done_ctr) {
                bar_sync<1, 256>();
                if (tid == 0) { asm volatile("fence.proxy.async.global;" ::: "memory"); fence_release_gpu(); red_add_gpu(done_ctr); }
                __syncwarp();
            }
        }
    }
    __syncthreads();
    asm volatile("griddepcontrol.wait;" ::: "memory");
    if (tid == 0) {
        __threadfence();
        if (atomicAdd(g_cnt + C_DONE, 1) == gridDim.x - 1) {
            for (int i = 0; i < C_NUM; i++) g_cnt[i] = 0;
            for (int i = 0; i < NSEG; i++) g_qready[i] = 0;
        }
    }
}

typedef CUresult (*EncodeFn)(CUtensorMap*, CUtensorMapDataType, cuuint32_t, void*, const cuuint64_t*, const cuuint64_t*, const cuuint32_t*,
                             const cuuint32_t*, CUtensorMapInterleave, CUtensorMapSwizzle, CUtensorMapL2promotion, CUtensorMapFloatOOBfill);
static void make_map(EncodeFn enc, CUtensorMap* m, const void* p, uint64_t cols, uint64_t rows, uint32_t bc, uint32_t br) {
    cuuint64_t dims[2] = {cols, rows}, strides[1] = {cols * 2};
    cuuint32_t box[2] = {bc, br}, es[2] = {1, 1};
    enc(m, CU_TENSOR_MAP_DATA_TYPE_BFLOAT16, 2, (void*)p, dims, strides, box, es, CU_TENSOR_MAP_INTERLEAVE_NONE, CU_TENSOR_MAP_SWIZZLE_128B,
        CU_TENSOR_MAP_L2_PROMOTION_L2_256B, CU_TENSOR_MAP_FLOAT_OOB_FILL_NONE);
}

static int h_poll_delay = POLL_DELAY, h_pdl = 1;
extern "C" void kernel_launch(void* const* d_in, const int* in_sizes, int n_in, void* d_out, int out_size) {
    const bf16 *x = (const bf16*)d_in[0], *mem0 = (const bf16*)d_in[1], *wq = (const bf16*)d_in[2], *wk = (const bf16*)d_in[3], *wv = (const bf16*)d_in[4],
               *wo = (const bf16*)d_in[5], *wg = (const bf16*)d_in[8], *wu = (const bf16*)d_in[9], *wd = (const bf16*)d_in[10], *gw = (const bf16*)d_in[11];
    static EncodeFn enc = nullptr;
    if (!enc) {
        void* fn = nullptr; cudaDriverEntryPointQueryResult qr;
        cudaGetDriverEntryPoint("cuTensorMapEncodeTiled", &fn, cudaEnableDefault, &qr);
        enc = (EncodeFn)fn;
        cudaFuncSetAttribute(rec_kernel, cudaFuncAttributeMaxDynamicSharedMemorySize, R_SMEM);
        cudaFuncSetAttribute(gemm_kernel, cudaFuncAttributeMaxDynamicSharedMemorySize, G_SMEM);
    }
    CUtensorMap tmX, tmWq, tmWk, tmWv, tmWo;
    {
        cuuint64_t dims[3] = {64, S_TOK, 10}, strides[2] = {DM * 2, 128};
        cuuint32_t box[3] = {64, 32, 5}, es[3] = {1, 1, 1};
        enc(&tmX, CU_TENSOR_MAP_DATA_TYPE_BFLOAT16, 3, (void*)x, dims, strides, box, es, CU_TENSOR_MAP_INTERLEAVE_NONE, CU_TENSOR_MAP_SWIZZLE_128B,
            CU_TENSOR_MAP_L2_PROMOTION_L2_256B, CU_TENSOR_MAP_FLOAT_OOB_FILL_NONE);
    }
    make_map(enc, &tmWq, wq, 4096, DM, 64, 160);
    make_map(enc, &tmWk, wk, 4096, DM, 64, 160);
    make_map(enc, &tmWv, wv, 4096, DM, 64, 160);
    make_map(enc, &tmWo, wo, DM, 4096, 64, 128);
    cudaStream_t st = cudaStreamPerThread;
    cudaLaunchConfig_t cfg = {};
    cfg.gridDim = dim3(96); cfg.blockDim = dim3(384); cfg.dynamicSmemBytes = R_SMEM; cfg.stream = st;
    cudaLaunchAttribute at[1];
    at[0].id = cudaLaunchAttributeClusterDimension; at[0].val.clusterDim.x = 3; at[0].val.clusterDim.y = 1; at[0].val.clusterDim.z = 1;
    cfg.attrs = at; cfg.numAttrs = 1;
    cudaLaunchKernelEx(&cfg, rec_kernel, tmX, tmWq, tmWk, tmWv, tmWo, mem0, h_poll_delay);
    CUtensorMap gX, gWg, gWu, gWo, gWd;
    make_map(enc, &gX, x, DM, S_TOK, 64, 128);
    make_map(enc, &gWg, wg, FF, DM, 64, 64);
    make_map(enc, &gWu, wu, FF, DM, 64, 64);
    make_map(enc, &gWo, wo, DM, 4096, 64, 64);
    make_map(enc, &gWd, wd, DM, FF, 64, 64);
    cudaLaunchConfig_t cg = {};
    cg.gridDim = dim3(132); cg.blockDim = dim3(288); cg.dynamicSmemBytes = G_SMEM; cg.stream = st;
    cudaLaunchAttribute ag[1];
    ag[0].id = cudaLaunchAttributeProgrammaticStreamSerialization; ag[0].val.programmaticStreamSerializationAllowed = 1;
    cg.attrs = ag; cg.numAttrs = h_pdl;
    cudaLaunchKernelEx(&cg, gemm_kernel, gX, gWg, gWu, gWo, gWd, x, gw, (bf16*)d_out);
}
```

```cpp
#include <cuda_runtime.h>
#include <cuda_bf16.h>
#include <cuda.h>
#include <stdint.h>

typedef __nv_bfloat16 bf16;

constexpr int S_TOK = 2048, DM = 640, NH = 32, DH = 128, NMEM = 8, SEG = 32, NSEG = 64, FF = 1728;
constexpr int KC_O = 64, KC_H = 27, KC_ALL = 91;

__device__ __align__(1024) uint32_t g_act[16 * KC_ALL * 4096];
constexpr int ACC_LINE = 24;
constexpr int ACC_SLOT = 96 * ACC_LINE;
__device__ __align__(1024) uint4 g_acc[8 * ACC_SLOT];
__device__ unsigned g_start;
constexpr int QKV_ITEM = 7680;
__device__ __align__(1024) uint32_t g_qkv[NSEG * NH * QKV_ITEM];
__device__ unsigned g_qready[NSEG];

__device__ __forceinline__ uint32_t smem_u32(const void* p) { return (uint32_t)__cvta_generic_to_shared(p); }
__device__ __forceinline__ uint32_t mapa(uint32_t a, uint32_t r) { uint32_t o; asm("mapa.shared::cluster.u32 %0, %1, %2;" : "=r"(o) : "r"(a), "r"(r)); return o; }
__device__ __forceinline__ void mbar_init(uint32_t b, int c) { asm volatile("mbarrier.init.shared::cta.b64 [%0], %1;" ::"r"(b), "r"(c) : "memory"); }
__device__ __forceinline__ void mbar_expect(uint32_t b, int bytes) { asm volatile("mbarrier.arrive.expect_tx.shared::cta.b64 _, [%0], %1;" ::"r"(b), "r"(bytes) : "memory"); }
__device__ __forceinline__ void mbar_arrive(uint32_t b) { asm volatile("mbarrier.arrive.shared::cta.b64 _, [%0];" ::"r"(b) : "memory"); }
__device__ __forceinline__ void mbar_wait(uint32_t b, int par) {
    asm volatile("{\n\t.reg .pred p;\n\t.reg .u32 n;\n\tmov.u32 n, 0;\n"
                 "WAIT_LOOP:\n\tmbarrier.try_wait.parity.shared::cta.b64 p, [%0], %1;\n\t@p bra.uni WAIT_DONE;\n\t"
                 "add.u32 n, n, 1;\n\tsetp.lt.u32 p, n, 4194304;\n\t@p bra.uni WAIT_LOOP;\n\ttrap;\n"
                 "WAIT_DONE:\n\t}" ::"r"(b), "r"(par) : "memory");
}
__device__ __forceinline__ void mbar_wait_cl(uint32_t b, int par) {
    asm volatile("{\n\t.reg .pred p;\n\t.reg .u32 n;\n\tmov.u32 n, 0;\n"
                 "WAIT_LOOP:\n\tmbarrier.try_wait.parity.relaxed.cluster.shared::cta.b64 p, [%0], %1;\n\t@p bra.uni WAIT_DONE;\n\t"
                 "add.u32 n, n, 1;\n\tsetp.lt.u32 p, n, 4194304;\n\t@p bra.uni WAIT_LOOP;\n\ttrap;\n"
                 "WAIT_DONE:\n\tfence.acquire.sync_restrict::shared::cluster.cluster;\n\t}" ::"r"(b), "r"(par) : "memory");
}
__device__ __forceinline__ void cluster_sync_relaxed() { asm volatile("barrier.cluster.arrive.relaxed.aligned; barrier.cluster.wait.aligned;" ::: "memory"); }
__device__ __forceinline__ void cluster_sync_all() { asm volatile("barrier.cluster.arrive.aligned; barrier.cluster.wait.aligned;" ::: "memory"); }
template <int ID, int N> __device__ __forceinline__ void bar_sync() { asm volatile("bar.sync %0, %1;" ::"n"(ID), "n"(N) : "memory"); }
template <int ID, int N> __device__ __forceinline__ void bar_arrive() { asm volatile("bar.arrive %0, %1;" ::"n"(ID), "n"(N) : "memory"); }
__device__ __forceinline__ void bar_sync_r(int id, int n) { asm volatile("bar.sync %0, %1;" ::"r"(id), "r"(n) : "memory"); }
__device__ __forceinline__ void fence_proxy_async() { asm volatile("fence.proxy.async.shared::cta;" ::: "memory"); }
__device__ __forceinline__ void fence_release_gpu() { asm volatile("fence.release.gpu;" ::: "memory"); }
__device__ __forceinline__ void red_add_gpu(unsigned* p) { asm volatile("red.relaxed.gpu.global.add.u32 [%0], 1;" ::"l"(p) : "memory"); }
__device__ __forceinline__ void tma3d_mc(uint32_t dst, const CUtensorMap* m, int c1, int c2, uint32_t bar, uint16_t mask) {
    asm volatile("cp.async.bulk.tensor.3d.shared::cluster.global.mbarrier::complete_tx::bytes.multicast::cluster [%0], [%1, {%3, %4, %5}], [%2], %6;"
                 ::"r"(dst), "l"(m), "r"(bar), "r"(0), "r"(c1), "r"(c2), "h"(mask) : "memory");
}
__device__ __forceinline__ void tma2d(uint32_t dst, const CUtensorMap* m, int c0, int c1, uint32_t bar) {
    asm volatile("cp.async.bulk.tensor.2d.shared::cluster.global.mbarrier::complete_tx::bytes [%0], [%1, {%3, %4}], [%2];"
                 ::"r"(dst), "l"(m), "r"(bar), "r"(c0), "r"(c1) : "memory");
}
__device__ __forceinline__ void tma2d_mc(uint32_t dst, const CUtensorMap* m, int c0, int c1, uint32_t bar, uint16_t mask) {
    asm volatile("cp.async.bulk.tensor.2d.shared::cluster.global.mbarrier::complete_tx::bytes.multicast::cluster [%0], [%1, {%3, %4}], [%2], %5;"
                 ::"r"(dst), "l"(m), "r"(bar), "r"(c0), "r"(c1), "h"(mask) : "memory");
}
__device__ __forceinline__ void tma2d_prefetch(const CUtensorMap* m, int c0, int c1) {
    asm volatile("cp.async.bulk.prefetch.tensor.2d.L2.global [%0, {%1, %2}];" ::"l"(m), "r"(c0), "r"(c1) : "memory");
}
__device__ __forceinline__ void bulk_s2c(uint32_t dst, uint32_t src, int bytes, uint32_t bar) {
    asm volatile("cp.async.bulk.shared::cluster.shared::cta.mbarrier::complete_tx::bytes [%0], [%1], %2, [%3];" ::"r"(dst), "r"(src), "r"(bytes), "r"(bar) : "memory");
}
__device__ __forceinline__ void bulk_s2g(void* dst, uint32_t src, int bytes) {
    asm volatile("cp.async.bulk.global.shared::cta.bulk_group [%0], [%1], %2;\n\tcp.async.bulk.commit_group;" ::"l"(dst), "r"(src), "r"(bytes) : "memory");
}
__device__ __forceinline__ void ldsm4(uint32_t* r, uint32_t a) { asm volatile("ldmatrix.sync.aligned.m8n8.x4.shared.b16 {%0,%1,%2,%3}, [%4];" : "=r"(r[0]), "=r"(r[1]), "=r"(r[2]), "=r"(r[3]) : "r"(a) : "memory"); }
__device__ __forceinline__ void ldsm4t(uint32_t* r, uint32_t a) { asm volatile("ldmatrix.sync.aligned.m8n8.x4.trans.shared.b16 {%0,%1,%2,%3}, [%4];" : "=r"(r[0]), "=r"(r[1]), "=r"(r[2]), "=r"(r[3]) : "r"(a) : "memory"); }
__device__ __forceinline__ void stsm4(uint32_t a, uint32_t r0, uint32_t r1, uint32_t r2, uint32_t r3) { asm volatile("stmatrix.sync.aligned.m8n8.x4.shared.b16 [%0], {%1,%2,%3,%4};" ::"r"(a), "r"(r0), "r"(r1), "r"(r2), "r"(r3) : "memory"); }
__device__ __forceinline__ void lds128(uint32_t* r, uint32_t a) { asm volatile("ld.shared.v4.u32 {%0,%1,%2,%3}, [%4];" : "=r"(r[0]), "=r"(r[1]), "=r"(r[2]), "=r"(r[3]) : "r"(a) : "memory"); }
__device__ __forceinline__ void lds128f(float* r, uint32_t a) { asm volatile("ld.shared.v4.f32 {%0,%1,%2,%3}, [%4];" : "=f"(r[0]), "=f"(r[1]), "=f"(r[2]), "=f"(r[3]) : "r"(a) : "memory"); }
__device__ __forceinline__ void lds64(uint32_t* r, uint32_t a) { asm volatile("ld.shared.v2.u32 {%0,%1}, [%2];" : "=r"(r[0]), "=r"(r[1]) : "r"(a) : "memory"); }
__device__ __forceinline__ void lds64f(float* r, uint32_t a) { asm volatile("ld.shared.v2.f32 {%0,%1}, [%2];" : "=f"(r[0]), "=f"(r[1]) : "r"(a) : "memory"); }
__device__ __forceinline__ void lds128fv(float* r, uint32_t a) { asm volatile("ld.volatile.shared.v4.f32 {%0,%1,%2,%3}, [%4];" : "=f"(r[0]), "=f"(r[1]), "=f"(r[2]), "=f"(r[3]) : "r"(a) : "memory"); }
__device__ __forceinline__ void lds64fv(float* r, uint32_t a) { asm volatile("ld.volatile.shared.v2.f32 {%0,%1}, [%2];" : "=f"(r[0]), "=f"(r[1]) : "r"(a) : "memory"); }
__device__ __forceinline__ void sts128(uint32_t a, uint32_t r0, uint32_t r1, uint32_t r2, uint32_t r3) { asm volatile("st.shared.v4.u32 [%0], {%1,%2,%3,%4};" ::"r"(a), "r"(r0), "r"(r1), "r"(r2), "r"(r3) : "memory"); }
__device__ __forceinline__ void sts128f(uint32_t a, float r0, float r1, float r2, float r3) { asm volatile("st.shared.v4.f32 [%0], {%1,%2,%3,%4};" ::"r"(a), "f"(r0), "f"(r1), "f"(r2), "f"(r3) : "memory"); }
__device__ __forceinline__ void st_async4(uint32_t a, uint32_t r0, uint32_t r1, uint32_t r2, uint32_t r3, uint32_t bar) {
    asm volatile("st.async.shared::cluster.mbarrier::complete_tx::bytes.v4.u32 [%0], {%1,%2,%3,%4}, [%5];" ::"r"(a), "r"(r0), "r"(r1), "r"(r2), "r"(r3), "r"(bar) : "memory");
}
__device__ __forceinline__ void st_async4f(uint32_t a, float r0, float r1, float r2, float r3, uint32_t bar) {
    st_async4(a, __float_as_uint(r0), __float_as_uint(r1), __float_as_uint(r2), __float_as_uint(r3), bar);
}
__device__ __forceinline__ void mma16816(float* d, const uint32_t* a, uint32_t b0, uint32_t b1) {
    asm volatile("mma.sync.aligned.m16n8k16.row.col.f32.bf16.bf16.f32 {%0,%1,%2,%3}, {%4,%5,%6,%7}, {%8,%9}, {%0,%1,%2,%3};"
                 : "+f"(d[0]), "+f"(d[1]), "+f"(d[2]), "+f"(d[3]) : "r"(a[0]), "r"(a[1]), "r"(a[2]), "r"(a[3]), "r"(b0), "r"(b1));
}
__device__ __forceinline__ void mma16816z(float* d, const uint32_t* a, uint32_t b0, uint32_t b1) {
    asm volatile("mma.sync.aligned.m16n8k16.row.col.f32.bf16.bf16.f32 {%0,%1,%2,%3}, {%4,%5,%6,%7}, {%8,%9}, {%10,%10,%10,%10};"
                 : "=f"(d[0]), "=f"(d[1]), "=f"(d[2]), "=f"(d[3]) : "r"(a[0]), "r"(a[1]), "r"(a[2]), "r"(a[3]), "r"(b0), "r"(b1), "f"(0.f));
}
__device__ __forceinline__ void mma1688(float* d, uint32_t a0, uint32_t a1, uint32_t b0) {
    asm volatile("mma.sync.aligned.m16n8k8.row.col.f32.bf16.bf16.f32 {%0,%1,%2,%3}, {%4,%5}, {%6}, {%0,%1,%2,%3};"
                 : "+f"(d[0]), "+f"(d[1]), "+f"(d[2]), "+f"(d[3]) : "r"(a0), "r"(a1), "r"(b0));
}
__device__ __forceinline__ void mma1688z(float* d, uint32_t a0, uint32_t a1, uint32_t b0) {
    asm volatile("mma.sync.aligned.m16n8k8.row.col.f32.bf16.bf16.f32 {%0,%1,%2,%3}, {%4,%5}, {%6}, {%7,%7,%7,%7};"
                 : "=f"(d[0]), "=f"(d[1]), "=f"(d[2]), "=f"(d[3]) : "r"(a0), "r"(a1), "r"(b0), "f"(0.f));
}
__device__ __forceinline__ void bar_arrive_r(int id, int n) { asm volatile("bar.arrive %0, %1;" ::"r"(id), "r"(n) : "memory"); }
#define SCHED_FENCE() asm volatile("{\n\t.reg .pred p;\n\tsetp.eq.s32 p, %0, %1;\n\t@p trap;\n\t}" ::"r"(poll_delay), "n"(-1 - __COUNTER__) : "memory")
__device__ __forceinline__ uint32_t pack2(float lo, float hi) { uint32_t r; asm("cvt.rn.bf16x2.f32 %0, %1, %2;" : "=r"(r) : "f"(hi), "f"(lo)); return r; }
__device__ __forceinline__ float ex2(float x) { float y; asm("ex2.approx.ftz.f32 %0, %1;" : "=f"(y) : "f"(x)); return y; }
__device__ __forceinline__ float rcp(float x) { float y; asm("rcp.approx.ftz.f32 %0, %1;" : "=f"(y) : "f"(x)); return y; }
#define WG_FENCE() asm volatile("wgmma.fence.sync.aligned;" ::: "memory")
#define WG_COMMIT() asm volatile("wgmma.commit_group.sync.aligned;" ::: "memory")
#define WG_WAIT0() asm volatile("wgmma.wait_group.sync.aligned 0;" ::: "memory")
template <int SC>
__device__ __forceinline__ void wgmma_n32_rs(float* d, const uint32_t* a, uint64_t desc) {
    asm volatile("wgmma.mma_async.sync.aligned.m64n32k16.f32.bf16.bf16 {%0,%1,%2,%3,%4,%5,%6,%7,%8,%9,%10,%11,%12,%13,%14,%15}, {%16,%17,%18,%19}, %20, %21, 1, 1, 0;"
                 : "+f"(d[0]), "+f"(d[1]), "+f"(d[2]), "+f"(d[3]), "+f"(d[4]), "+f"(d[5]), "+f"(d[6]), "+f"(d[7]),
                   "+f"(d[8]), "+f"(d[9]), "+f"(d[10]), "+f"(d[11]), "+f"(d[12]), "+f"(d[13]), "+f"(d[14]), "+f"(d[15])
                 : "r"(a[0]), "r"(a[1]), "r"(a[2]), "r"(a[3]), "l"(desc), "n"(SC));
}
__device__ __forceinline__ void wgmma_n32_rs_z(float* d, const uint32_t* a, uint64_t desc) {
    asm volatile("wgmma.mma_async.sync.aligned.m64n32k16.f32.bf16.bf16 {%0,%1,%2,%3,%4,%5,%6,%7,%8,%9,%10,%11,%12,%13,%14,%15}, {%16,%17,%18,%19}, %20, 0, 1, 1, 0;"
                 : "=f"(d[0]), "=f"(d[1]), "=f"(d[2]), "=f"(d[3]), "=f"(d[4]), "=f"(d[5]), "=f"(d[6]), "=f"(d[7]),
                   "=f"(d[8]), "=f"(d[9]), "=f"(d[10]), "=f"(d[11]), "=f"(d[12]), "=f"(d[13]), "=f"(d[14]), "=f"(d[15])
                 : "r"(a[0]), "r"(a[1]), "r"(a[2]), "r"(a[3]), "l"(desc));
}
template <int SC>
__device__ __forceinline__ void wgmma_n24_tt(float* d, uint64_t da, uint64_t db) {
    asm volatile("wgmma.mma_async.sync.aligned.m64n24k16.f32.bf16.bf16 {%0,%1,%2,%3,%4,%5,%6,%7,%8,%9,%10,%11}, %12, %13, %14, 1, 1, 1, 1;"
                 : "+f"(d[0]), "+f"(d[1]), "+f"(d[2]), "+f"(d[3]), "+f"(d[4]), "+f"(d[5]), "+f"(d[6]), "+f"(d[7]),
                   "+f"(d[8]), "+f"(d[9]), "+f"(d[10]), "+f"(d[11])
                 : "l"(da), "l"(db), "n"(SC));
}
template <int SC>
__device__ __forceinline__ void wgmma_n32_ss(float* d, uint64_t da, uint64_t db) {
    asm volatile("wgmma.mma_async.sync.aligned.m64n32k16.f32.bf16.bf16 {%0,%1,%2,%3,%4,%5,%6,%7,%8,%9,%10,%11,%12,%13,%14,%15}, %16, %17, %18, 1, 1, 0, 0;"
                 : "+f"(d[0]), "+f"(d[1]), "+f"(d[2]), "+f"(d[3]), "+f"(d[4]), "+f"(d[5]), "+f"(d[6]), "+f"(d[7]),
                   "+f"(d[8]), "+f"(d[9]), "+f"(d[10]), "+f"(d[11]), "+f"(d[12]), "+f"(d[13]), "+f"(d[14]), "+f"(d[15])
                 : "l"(da), "l"(db), "n"(SC));
}
__device__ __forceinline__ void wgmma_n24_tt_z(float* d, uint64_t da, uint64_t db) {
    asm volatile("wgmma.mma_async.sync.aligned.m64n24k16.f32.bf16.bf16 {%0,%1,%2,%3,%4,%5,%6,%7,%8,%9,%10,%11}, %12, %13, 0, 1, 1, 1, 1;"
                 : "=f"(d[0]), "=f"(d[1]), "=f"(d[2]), "=f"(d[3]), "=f"(d[4]), "=f"(d[5]), "=f"(d[6]), "=f"(d[7]),
                   "=f"(d[8]), "=f"(d[9]), "=f"(d[10]), "=f"(d[11])
                 : "l"(da), "l"(db));
}
__device__ __forceinline__ void wgmma_n32_ss_z(float* d, uint64_t da, uint64_t db) {
    asm volatile("wgmma.mma_async.sync.aligned.m64n32k16.f32.bf16.bf16 {%0,%1,%2,%3,%4,%5,%6,%7,%8,%9,%10,%11,%12,%13,%14,%15}, %16, %17, 0, 1, 1, 0, 0;"
                 : "=f"(d[0]), "=f"(d[1]), "=f"(d[2]), "=f"(d[3]), "=f"(d[4]), "=f"(d[5]), "=f"(d[6]), "=f"(d[7]),
                   "=f"(d[8]), "=f"(d[9]), "=f"(d[10]), "=f"(d[11]), "=f"(d[12]), "=f"(d[13]), "=f"(d[14]), "=f"(d[15])
                 : "l"(da), "l"(db));
}
__device__ __forceinline__ uint64_t mkdesc(uint32_t addr, uint32_t lbo, uint32_t sbo) {
    return (uint64_t)((addr & 0x3FFFF) >> 4) | ((uint64_t)(lbo >> 4) << 16) | ((uint64_t)(sbo >> 4) << 32);
}
__device__ __forceinline__ int clk32() { unsigned long long t; asm volatile("mov.u64 %0, %%clock64;" : "=l"(t)::"memory"); return (int)t; }
__device__ __forceinline__ void spin_until(int t1, const void* keep) {
    asm volatile("{\n\t.reg .pred p;\n\t.reg .u64 t;\n\t.reg .s32 a, b;\n"
                 "SPIN:\n\tmov.u64 t, %%clock64;\n\tcvt.u32.u64 a, t;\n\tsub.s32 b, a, %0;\n\tsetp.lt.s32 p, b, 0;\n\t@p bra.uni SPIN;\n\t}" ::"r"(t1), "l"(keep) : "memory");
}

constexpr int R_XB = 0;
constexpr int R_WO = 81920;
constexpr int R_VT = 147456;
constexpr int R_QK = 167936;
constexpr int R_VS = R_QK;
constexpr int R_QS = 188416;
constexpr int R_MEM = 190464;
constexpr int R_VM = 201216;
constexpr int R_SMSG = 203264;
constexpr int R_OB = 206336;
constexpr int R_SUM = R_OB + 2048;
constexpr int R_EX = 208896;
constexpr int R_ZERO = 217088 + 128;
constexpr int R_BAR = 217088;
constexpr int R_WST = 40960;
constexpr int R_SMEM = 217344 + 1024 + 6656;
enum { B_W0 = 0, B_X0 = 4, B_WO = 6, B_S = 7, B_V = 8, B_VX = 9, B_XF = 10, B_NUM = 11 };
enum { NB_MEM = 1, NB_QK = 2, NB_O = 3, NB_EX = 4, NB_EPI = 6, NB_SENT = 7, NB_PAIR = 8, NB_VC = 12 };
#define POLL_DELAY 1150
#define TS(i)
#define TSD(i, dep)

__device__ __forceinline__ uint32_t pin(uint32_t v) { return __shfl_sync(~0u, v, threadIdx.x & 31); }
__device__ __forceinline__ void st_async2f(uint32_t a, float r0, float r1, uint32_t bar) {
    asm volatile("st.async.shared::cluster.mbarrier::complete_tx::bytes.v2.f32 [%0], {%1,%2}, [%3];" ::"r"(a), "f"(r0), "f"(r1), "r"(bar) : "memory");
}

#define GK1 20
#define GK2 8
#define GK3 20
#define XMODE 2
__device__ __forceinline__ void xload(const uint32_t sb, const CUtensorMap* tmX, int s, int rank, int head) {
    mbar_expect(sb + R_BAR + 8 * (B_X0 + (s & 1)), 40960);
    if (rank < 2) {
        tma3d_mc(sb + R_XB + (s & 1) * 40960 + rank * 20480, tmX, (s + 2) * SEG, rank * 5, sb + R_BAR + 8 * (B_X0 + (s & 1)), 7);
        if (head == (s & 31) && s + 4 < NSEG)
            asm volatile("cp.async.bulk.prefetch.tensor.3d.L2.global [%0, {%1, %2, %3}];" ::"l"(tmX), "r"(0), "r"((s + 4) * SEG), "r"(rank * 5) : "memory");
    }
}

template <int RANK>
__device__ __forceinline__ void aux_loop(const uint32_t sb, const int head, const CUtensorMap* tmX, const int poll_delay) {
    constexpr bool ISV = RANK == 2;
    const uint32_t bars = sb + R_BAR;
    const float SC = 0.08838834764831845f * 1.4426950408889634f;
    const int w = __shfl_sync(~0u, (threadIdx.x >> 5) & 3, 0);
    uint32_t l16 = pin(sb + (threadIdx.x & 31) * 16);
#define LOCAL() asm volatile("" : "+r"(l16))
#define first (w == 0 && l16 == sb)
#define LANE ((l16 >> 4) & 31)
#define TSW (8 + w)
    uint32_t vto = 0;
    if (ISV) {
        bar_sync<NB_QK, 384>();
        if (first) {
            bulk_s2c(mapa(sb + R_VT, 0), sb + R_VT, 8192, mapa(bars + 8 * B_VX, 0));
            bulk_s2c(mapa(sb + R_VT, 1), sb + R_VT, 8192, mapa(bars + 8 * B_VX, 1));
        }
        __syncwarp();
    }
#pragma unroll 1
    for (int s = 0;; s++) {
        if (ISV || w == 3) bar_arrive<NB_MEM, 384>();
        else bar_sync<NB_MEM, 384>();
        LOCAL();
        if (first && s < NSEG - 1) {
            mbar_expect(bars + 8 * B_S, ISV ? 2560 : 1280);
            if (!ISV) { mbar_expect(bars + 8 * B_V, 2048); mbar_expect(bars + 8 * B_VX, 8192); }
        }
        __syncwarp();
        if (w == 3) {
            asm volatile("cp.async.bulk.wait_group 0;\n\tfence.proxy.async.global;" ::: "memory");
            if (l16 == sb && s > 0 && s < NSEG - 1) red_add_gpu(&g_qready[s - 1]);
            if (RANK == 0 && s == 8 && head == 0 && LANE == 0) g_start = 0;
            __syncwarp();
        }
        if (s == NSEG - 1) break;
        if (!ISV) mbar_wait_cl(bars + 8 * B_VX, s & 1);
        if (!ISV) {
            const uint32_t sbar = bars + 8 * B_S, sa = l16 + w * 512 + R_SMSG + RANK * 1536;
            if (w < 2) {
                uint32_t kf[4][4], qf[4][4];
#pragma unroll
                for (int k = 0; k < 4; k++) ldsm4t(kf[k], l16 + (s & 1) * 10240 + w * 512 + R_QK + 4096 + k * 1024);
                bar_sync<NB_QK, 352>();
#pragma unroll
                for (int k = 0; k < 4; k++) ldsm4t(qf[k], l16 + R_QS + k * 512);
                SCHED_FENCE();
                float e0[2][4], e1[2][4];
                mma16816z(e0[0], qf[0], kf[0][0], kf[0][1]); mma16816z(e1[0], qf[0], kf[0][2], kf[0][3]);
                mma16816z(e0[1], qf[1], kf[1][0], kf[1][1]); mma16816z(e1[1], qf[1], kf[1][2], kf[1][3]);
                mma16816(e0[0], qf[2], kf[2][0], kf[2][1]); mma16816(e1[0], qf[2], kf[2][2], kf[2][3]);
                mma16816(e0[1], qf[3], kf[3][0], kf[3][1]); mma16816(e1[1], qf[3], kf[3][2], kf[3][3]);
                const float v0 = (e0[0][0] + e0[0][2]) + (e0[1][0] + e0[1][2]), v1 = (e0[0][1] + e0[0][3]) + (e0[1][1] + e0[1][3]);
                const float v2 = (e1[0][0] + e1[0][2]) + (e1[1][0] + e1[1][2]), v3 = (e1[0][1] + e1[0][3]) + (e1[1][1] + e1[1][3]);
                st_async4f(mapa(sa, 1 - RANK), v0, v1, v2, v3, mapa(sbar, 1 - RANK));
                st_async4f(mapa(sa, 2), v0, v1, v2, v3, mapa(sbar, 2));
                sts128f(sa, v0, v1, v2, v3);
                __syncwarp();
                if (l16 == sb) mbar_arrive(sbar);
                TS(1);
            } else if (w == 2) {
                uint32_t kf[4][4], qf[4][4];
                bar_sync<NB_QK, 352>();
#pragma unroll
                for (int k = 0; k < 4; k++) { ldsm4t(qf[k], l16 + R_QS + k * 512); ldsm4t(kf[k], l16 + (s & 1) * 10240 + R_QK + 8192 + k * 512); }
                SCHED_FENCE();
                float e0[2][4], e1[2][4];
                mma16816z(e0[0], qf[0], kf[0][0], kf[0][1]); mma16816z(e1[0], qf[0], kf[0][2], kf[0][3]);
                mma16816z(e0[1], qf[1], kf[1][0], kf[1][1]); mma16816z(e1[1], qf[1], kf[1][2], kf[1][3]);
                mma16816(e0[0], qf[2], kf[2][0], kf[2][1]); mma16816(e1[0], qf[2], kf[2][2], kf[2][3]);
                mma16816(e0[1], qf[3], kf[3][0], kf[3][1]); mma16816(e1[1], qf[3], kf[3][2], kf[3][3]);
                const float v0 = ((e0[0][0] + e0[0][2]) + (e1[0][0] + e1[0][2])) + ((e0[1][0] + e0[1][2]) + (e1[1][0] + e1[1][2]));
                const float v1 = ((e0[0][1] + e0[0][3]) + (e1[0][1] + e1[0][3])) + ((e0[1][1] + e0[1][3]) + (e1[1][1] + e1[1][3]));
                st_async2f(mapa(sa, 1 - RANK), v0, v1, mapa(sbar, 1 - RANK));
                st_async2f(mapa(sa, 2), v0, v1, mapa(sbar, 2));
                asm volatile("st.shared.v2.f32 [%0], {%1,%2};" ::"r"(sa), "f"(v0), "f"(v1) : "memory");
                __syncwarp();
                if (l16 == sb) mbar_arrive(sbar);
                TS(1);
            }
        }
        uint32_t va[2][2][4], vm[4];
        {
            const uint32_t a = (l16 & ~0x180u) + ((l16 & 128) << 2) + ((l16 & 256) >> 1) + w * 1024 + vto + R_VT;
#pragma unroll
            for (int T = 0; T < 2; T++)
#pragma unroll
                for (int k = 0; k < 2; k++) ldsm4(va[T][k], a + T * 4096 + k * 256);
        }
        if (!ISV && w < 3) bar_arrive<NB_SENT, 352>();
        const uint32_t vma = (l16 & ~0x100u) + ((l16 & 256) << 2) + w * 256 + R_VT + 8192 + vto;
        if (ISV) { bar_sync<NB_QK, 384>(); ldsm4(vm, vma); }
        if (s == NSEG - 2 && w == 3) {
            bar_sync<NB_VC, 288>();
            if (l16 == sb) bulk_s2g(g_qkv + (s * NH + head) * QKV_ITEM + RANK * 2560, sb + (ISV ? R_VT : R_QK) + vto, 10240);
            __syncwarp();
        }
        mbar_wait_cl(bars + 8 * B_S, s & 1);
        TS(2);
        float sv[10], b[10];
        lds128fv(sv, l16 + R_SMSG); lds128fv(b, l16 + R_SMSG + 1536);
        lds128fv(sv + 4, l16 + R_SMSG + 512); lds128fv(b + 4, l16 + R_SMSG + 2048);
        lds64fv(sv + 8, l16 + R_SMSG + 1024); lds64fv(b + 8, l16 + R_SMSG + 2560);
        SCHED_FENCE();
#pragma unroll
        for (int e = 0; e < 10; e++) sv[e] += b[e];
        float mx = fmaxf(fmaxf(fmaxf(sv[0], sv[1]), fmaxf(sv[2], sv[3])), fmaxf(fmaxf(sv[4], sv[5]), fmaxf(sv[6], sv[7])));
        mx = fmaxf(mx, fmaxf(sv[8], sv[9]));
        mx = fmaxf(mx, __shfl_xor_sync(~0u, mx, 1));
        uint32_t vok = 1;
        if (!ISV) asm volatile("{.reg .pred p; mbarrier.test_wait.parity.relaxed.cluster.shared::cta.b64 p, [%1], %2; selp.u32 %0, 1, 0, p;}" : "=r"(vok) : "r"(bars + 8 * B_V), "r"(s & 1) : "memory");
        mx = fmaxf(mx, __shfl_xor_sync(~0u, mx, 2));
        mx *= -SC;
        float oa[2][4], sm[4];
        {
            const uint32_t one = 0x3F803F80u;
            const uint32_t ones[4] = {one, one, one, one};
            if (!ISV) {
                if (!__all_sync(~0u, vok)) mbar_wait_cl(bars + 8 * B_V, s & 1);
                asm volatile("fence.acquire.sync_restrict::shared::cluster.cluster;" ::: "memory");
                ldsm4(vm, vma);
            }
            const uint32_t p0 = pack2(ex2(fmaf(sv[0], SC, mx)), ex2(fmaf(sv[1], SC, mx))), p1 = pack2(ex2(fmaf(sv[2], SC, mx)), ex2(fmaf(sv[3], SC, mx)));
            mma16816z(oa[0], va[0][0], p0, p1); mma16816z(oa[1], va[1][0], p0, p1); mma16816z(sm, ones, p0, p1);
            const uint32_t p4 = pack2(ex2(fmaf(sv[8], SC, mx)), ex2(fmaf(sv[9], SC, mx)));
            mma1688(oa[0], vm[0], vm[1], p4); mma1688(oa[1], vm[2], vm[3], p4); mma1688(sm, one, one, p4);
            const uint32_t p2 = pack2(ex2(fmaf(sv[4], SC, mx)), ex2(fmaf(sv[5], SC, mx))), p3 = pack2(ex2(fmaf(sv[6], SC, mx)), ex2(fmaf(sv[7], SC, mx)));
            mma16816(oa[0], va[0][1], p2, p3); mma16816(oa[1], va[1][1], p2, p3); mma16816(sm, ones, p2, p3);
        }
        stsm4(l16 + w * 512 + R_OB, pack2(oa[0][0], oa[0][1]), pack2(oa[0][2], oa[0][3]), pack2(oa[1][0], oa[1][1]), pack2(oa[1][2], oa[1][3]));
        if (w == 0) asm volatile("st.shared.v2.f32 [%0], {%1,%2};" ::"r"(l16 + R_SUM), "f"(sm[0]), "f"(sm[1]) : "memory");
        bar_sync<NB_O, 384>();
        TS(3);
        const int tO = clk32();
        if (s == NSEG - 2 && w == 3) {
            asm volatile("cp.async.bulk.wait_group 0;\n\tfence.proxy.async.global;" ::: "memory");
            if (l16 == sb) red_add_gpu(&g_qready[s]);
            __syncwarp();
        }
        vto = ISV ? (vto == 20480 ? 0 : vto + 10240) : 10240 - vto;
        const uint4* ap = g_acc + (s & 7) * ACC_SLOT + (w * 24 + (LANE >> 3)) * ACC_LINE + (LANE & 3) * 2 + ((LANE >> 2) & 1);
        const bool odd = (l16 >> 6) & 1;
        const uint32_t st1 = l16 + R_MEM + w * 2688 + (LANE >= 24 ? 384 : 0), st2 = l16 + R_MEM + w * 2688 + 384;
        spin_until(tO + poll_delay, ap);
        TS(4);
        int lim = 0;
        while (true) {
            uint4 a[6];
#pragma unroll
            for (int i = 0; i < 6; i++)
                asm volatile("ld.relaxed.gpu.global.v4.u32 {%0,%1,%2,%3}, [%4];" : "=r"(a[i].x), "=r"(a[i].y), "=r"(a[i].z), "=r"(a[i].w)
                             : "l"(ap + i * 4 * ACC_LINE) : "memory");
            if (ISV && lim == 0 && w < 2 && s + 1 < NSEG - 1) {
                if (l16 == sb) bulk_s2c(mapa(sb + R_VT + ((s + 1) & 1) * 10240, w), sb + R_VT + vto, 8192, mapa(bars + 8 * B_VX, w));
                __syncwarp();
            }
            if (lim == 0 && w == 3 && s < NSEG - 2) {
                if (l16 == sb) bulk_s2g(g_qkv + (s * NH + head) * QKV_ITEM + RANK * 2560, sb + (ISV ? R_VT + (vto == 0 ? 20480 : vto - 10240) : R_QK + 10240 - vto), 10240);
                if (l16 == sb) bulk_s2g(g_acc + ((s + 4) & 7) * ACC_SLOT + (head * 3 + RANK) * ACC_LINE, sb + R_ZERO, 128);
                __syncwarp();
            }
            uint32_t bad = 0;
#pragma unroll
            for (int i = 0; i < 3; i++) {
                bad |= (odd ? a[2 * i].w : a[2 * i + 1].w) ^ 0x42004200u;
                const uint32_t mg = odd ? a[2 * i + 1].w : a[2 * i].w;
                stsm4(st1 + i * 896, a[2 * i].x, a[2 * i].y, a[2 * i].z, mg);
                stsm4(st2 + i * 896, a[2 * i + 1].x, a[2 * i + 1].y, a[2 * i + 1].z, mg);
            }
            if (__all_sync(~0u, bad == 0)) break;
            if (++lim > (1 << 20)) __trap();
        }
        TS(5);
    }
#undef LANE
#undef TSW
#define TSW warp
#undef first
}

#define KEEP12(x) asm volatile("" : "+f"(x[0]), "+f"(x[1]), "+f"(x[2]), "+f"(x[3]), "+f"(x[4]), "+f"(x[5]), "+f"(x[6]), "+f"(x[7]), \
                                    "+f"(x[8]), "+f"(x[9]), "+f"(x[10]), "+f"(x[11])::"memory")
#define KEEP16(x) asm volatile("" : "+f"(x[0]), "+f"(x[1]), "+f"(x[2]), "+f"(x[3]), "+f"(x[4]), "+f"(x[5]), "+f"(x[6]), "+f"(x[7]), \
                                    "+f"(x[8]), "+f"(x[9]), "+f"(x[10]), "+f"(x[11]), "+f"(x[12]), "+f"(x[13]), "+f"(x[14]), "+f"(x[15])::"memory")

template <int RANK>
__device__ __forceinline__ void main_loop(const uint32_t sb, const int head, const int warp, const uint32_t (&wk_)[20][4], const uint32_t (&ws_)[20][4], const CUtensorMap* tmX, const int poll_delay) {
    const uint32_t bars = sb + R_BAR;
    constexpr bool ISV = RANK == 2;
    constexpr int rank = RANK;
    const int j = warp >> 2, w = warp & 3;
    uint32_t l16 = pin(sb + (threadIdx.x & 31) * 16);
    uint32_t cst, wo0, wo1;
    const uint4* rp;
    {
        const int lane = threadIdx.x & 31, m = lane >> 3, r8 = lane & 7;
        const int isk = (lane >> 4) ^ j, hi = (lane >> 3) & 1;
        cst = pin(sb + w * 512 + r8 * 16 + (isk ? R_QK + 8192 + j * 256 + hi * 128 : R_QS + j * 128 + hi * 256));
        const int gb = (warp >> 1) * 7 + (warp & 1) * 3;
        const int G0 = gb + (m & 1);
        const int G1 = (m & 1) ? (warp >> 1) * 7 + 6 : gb + 2;
        const uint32_t rowo = sb + R_WO + ((m >> 1) * 8 + r8) * 128;
        wo0 = pin(rowo + (G0 >> 3) * 16384 + (((G0 & 7) ^ r8) << 4));
        wo1 = pin(rowo + (G1 >> 3) * 16384 + (((G1 & 7) ^ r8) << 4));
        rp = g_acc + pin(((rank * 8 + warp) * 4 + m) * ACC_LINE + (lane & 3) * 2 + ((lane >> 2) & 1));
    }

    auto xdesc = [&](int t) { return mkdesc(sb + R_XB + (t & 1) * 40960 + j * 20480, 16, 1024) | (1ull << 62); };
    auto put_partial = [&](float* xs) {
        const uint32_t ex = l16 + R_EX + warp * 1024;
        sts128(ex, pack2(xs[0], xs[1]), pack2(xs[2], xs[3]), pack2(xs[4], xs[5]), pack2(xs[6], xs[7]));
        sts128(ex + 512, pack2(xs[8], xs[9]), pack2(xs[10], xs[11]), pack2(xs[12], xs[13]), pack2(xs[14], xs[15]));
    };
    uint32_t f0[5][4], f1[5][4];
    uint32_t vto = 0;
    auto vproject = [&](int t) {
        float xk[16];
        const uint64_t d1 = mkdesc(sb + R_XB + (t & 1) * 40960, 16, 1024) | (1ull << 62);
        if (t < NSEG) mbar_wait(bars + 8 * (B_X0 + (t & 1)), (t >> 1) & 1);
        WG_FENCE();
#pragma unroll
        for (int k = 0; k < 40; k++) {
            const uint64_t dk = d1 + (uint64_t)(((k >> 2) * 4096 + (k & 3) * 32) >> 4);
            if (k == 0) wgmma_n32_rs_z(xk, wk_[0], dk); else wgmma_n32_rs<1>(xk, k < 20 ? wk_[k % 20] : ws_[k % 20], dk);
            if (k == 4) { ldsm4t(f0[0], wo0); ldsm4t(f1[0], wo1); ldsm4t(f0[1], wo0 + 4 * 2048); ldsm4t(f1[1], wo1 + 4 * 2048); }
        }
        WG_COMMIT();
        const uint32_t dst = l16 + R_VT + vto + warp * 1024;
        vto = vto == 20480 ? 0 : vto + 10240;
        WG_WAIT0();
        KEEP16(xk);
        stsm4(dst, pack2(xk[0], xk[1]), pack2(xk[4], xk[5]), pack2(xk[8], xk[9]), pack2(xk[12], xk[13]));
        stsm4(dst + 512, pack2(xk[2], xk[3]), pack2(xk[6], xk[7]), pack2(xk[10], xk[11]), pack2(xk[14], xk[15]));
    };
    auto window = [&](int t) {
        if (ISV) { vproject(t + 1); return; }
        float xs[16], xk[16];
        uint32_t o[8], pk[8];
        lds128(o, l16 + R_EX + (warp ^ 4) * 1024); lds128(o + 4, l16 + R_EX + (warp ^ 4) * 1024 + 512);
        const uint64_t d1 = xdesc(t), d2 = xdesc(t + 1);
        WG_FENCE();
#pragma unroll
        for (int k = 0; k < GK1; k++) {
            const uint64_t dk = d1 + (uint64_t)(((k >> 2) * 4096 + (k & 3) * 32) >> 4);
            if (k == 0) wgmma_n32_rs_z(xk, wk_[k], dk); else wgmma_n32_rs<1>(xk, wk_[k], dk);
        }
        WG_COMMIT();
        if (t + 1 < NSEG) mbar_wait(bars + 8 * (B_X0 + ((t + 1) & 1)), ((t + 1) >> 1) & 1);
#pragma unroll
        for (int k = 0; k < GK2; k++) {
            const uint64_t dk = d2 + (uint64_t)(((k >> 2) * 4096 + (k & 3) * 32) >> 4);
            if (k == 0) wgmma_n32_rs_z(xs, ws_[k], dk); else wgmma_n32_rs<1>(xs, ws_[k], dk);
        }
        WG_COMMIT();
        asm volatile("wgmma.wait_group.sync.aligned 1;" ::: "memory");
        KEEP16(xk);
#pragma unroll
        for (int i = 0; i < 8; i++) pk[i] = pack2(xk[2 * i] + __uint_as_float(o[i] << 16), xk[2 * i + 1] + __uint_as_float(o[i] & 0xFFFF0000u));
        bar_arrive_r(NB_EX + j, 256);
        {
            const uint32_t dst = l16 + R_QK + (t & 1) * 10240 + warp * 1024;
            stsm4(dst, pk[0], pk[1], pk[2], pk[3]); stsm4(dst + 512, pk[4], pk[5], pk[6], pk[7]);
        }
#pragma unroll
        for (int k = 8; k < GK3; k++) {
            const uint64_t dk = d2 + (uint64_t)(((k >> 2) * 4096 + (k & 3) * 32) >> 4);
            wgmma_n32_rs<1>(xs, ws_[k], dk);
        }
        WG_COMMIT();
        bar_sync_r(NB_EX + 1 - j, 256);
        WG_WAIT0();
        KEEP16(xs);
        put_partial(xs);
    };
    if (ISV) {
        vproject(0);
        fence_proxy_async();
        bar_arrive<NB_QK, 384>();
        mbar_wait(bars + 8 * B_WO, 0);
    } else {
        float xs[16];
        const uint64_t d2 = xdesc(0);
        mbar_wait(bars + 8 * B_X0, 0);
        WG_FENCE();
#pragma unroll
        for (int k = 0; k < 20; k++) {
            const uint64_t dk = d2 + (uint64_t)(((k >> 2) * 4096 + (k & 3) * 32) >> 4);
            if (k == 0) wgmma_n32_rs_z(xs, ws_[k], dk); else wgmma_n32_rs<1>(xs, ws_[k], dk);
        }
        WG_COMMIT();
        WG_WAIT0();
        KEEP16(xs);
        put_partial(xs);
        mbar_wait(bars + 8 * (B_X0 + 1), 0);
        mbar_wait(bars + 8 * B_WO, 0);
        bar_sync<NB_EPI, 256>();
    }
#pragma unroll 1
    for (int s = -1;;) {
        window(s + 1);
        TS(4);
        s++;
        LOCAL();
        bar_sync<NB_MEM, 384>();
        {
            float ca[2][4], cb[2][4];
#pragma unroll
            for (int i = 0; i < 10; i++) {
                uint32_t b[4], b2[4];
                ldsm4t(b, l16 + R_MEM + (ISV ? 0 : j * 5120) + i * 512);
                if (ISV) ldsm4t(b2, l16 + R_MEM + 5120 + i * 512);
                const uint32_t* bs = ISV ? b2 : b;
                if (i == 1) TS(0);
                if (!ISV) {
                    if (i == 3) ldsm4t(f0[0], wo0);
                    if (i == 5) ldsm4t(f1[0], wo1);
                    if (i == 7) ldsm4t(f0[1], wo0 + 4 * 2048);
                    if (i == 9) ldsm4t(f1[1], wo1 + 4 * 2048);
                }
                if (i == 0) {
                    mma16816z(ca[0], wk_[0], b[0], b[1]); mma16816z(cb[0], ws_[0], bs[0], bs[1]);
                    mma16816z(ca[1], wk_[1], b[2], b[3]); mma16816z(cb[1], ws_[1], bs[2], bs[3]);
                } else {
                    mma16816(ca[0], wk_[2 * i], b[0], b[1]); mma16816(cb[0], ws_[2 * i], bs[0], bs[1]);
                    mma16816(ca[1], wk_[2 * i + 1], b[2], b[3]); mma16816(cb[1], ws_[2 * i + 1], bs[2], bs[3]);
                }
            }
#pragma unroll
            for (int e = 0; e < 4; e++) { ca[0][e] += ca[1][e]; cb[0][e] += cb[1][e]; }
            if (!ISV) {
                stsm4(cst, pack2(ca[0][0], ca[0][1]), pack2(ca[0][2], ca[0][3]), pack2(cb[0][0], cb[0][1]), pack2(cb[0][2], cb[0][3]));
                if (s < NSEG - 1) bar_arrive<NB_QK, 352>();
                if (cst < sb + R_QS) cst += (s & 1) ? -10240 : 10240;
            } else {
                const uint32_t row = (l16 & ~0x100u) + warp * 256 + R_VT + 8192;
                const uint32_t loc = row + (vto == 20480 ? 0 : vto + 10240);
                asm volatile("stmatrix.sync.aligned.m8n8.x2.shared.b16 [%0], {%1,%2};" ::"r"(loc), "r"(pack2(ca[0][0] + cb[0][0], ca[0][1] + cb[0][1])),
                             "r"(pack2(ca[0][2] + cb[0][2], ca[0][3] + cb[0][3])) : "memory");
                if (s < NSEG - 1) {
                    uint32_t r[4];
                    __syncwarp();
                    lds128(r, loc);
                    const uint32_t peer = (l16 >> 8) & 1;
                    st_async4(mapa(row + (s & 1) * 10240, peer), r[0], r[1], r[2], r[3], mapa(bars + 8 * B_V, peer));
                    bar_arrive<NB_QK, 384>();
                }
            }
            TS(1);
            fence_proxy_async();
            if (s == NSEG - 2) bar_arrive<NB_VC, 288>();
        }
        if (s == NSEG - 1) break;
        {
            if (!ISV) bar_sync<NB_SENT, 352>();
            ldsm4t(f0[2], wo0 + 1 * 2048); ldsm4t(f1[2], wo1 + 1 * 2048);
            ldsm4t(f0[3], wo0 + 5 * 2048); ldsm4t(f1[3], wo1 + 5 * 2048);
            ldsm4t(f0[4], wo0 + 2 * 2048); ldsm4t(f1[4], wo1 + 2 * 2048);
            if (warp == 0 && s + 2 < NSEG) {
                mbar_wait_cl(bars + 8 * B_S, s & 1);
                if (!ISV) mbar_wait_cl(bars + 8 * B_V, s & 1);
                if (l16 == sb) xload(sb, tmX, s, RANK, head);
                __syncwarp();
            }
            bar_sync<NB_O, 384>();
            float d0[4], d1[4];
            uint32_t b0[4], b1[4], b2[4];
            ldsm4t(b0, l16 + R_OB); ldsm4t(b1, l16 + R_OB + 512);
            SCHED_FENCE();
            TS(2);
            mma16816z(d0, f0[0], b0[0], b0[1]); mma16816z(d1, f1[0], b0[0], b0[1]);
            ldsm4t(b2, l16 + R_OB + 1024);
            mma16816(d0, f0[1], b0[2], b0[3]); mma16816(d1, f1[1], b0[2], b0[3]);
            ldsm4t(f0[1], wo0 + 6 * 2048); ldsm4t(f1[1], wo1 + 6 * 2048); ldsm4t(b0, l16 + R_OB + 1536);
            mma16816(d0, f0[2], b1[0], b1[1]); mma16816(d1, f1[2], b1[0], b1[1]);
            ldsm4t(f0[2], wo0 + 3 * 2048); ldsm4t(f1[2], wo1 + 3 * 2048);
            mma16816(d0, f0[3], b1[2], b1[3]); mma16816(d1, f1[3], b1[2], b1[3]);
            ldsm4t(f0[3], wo0 + 7 * 2048); ldsm4t(f1[3], wo1 + 7 * 2048);
            float sm[2];
            lds64f(sm, l16 + R_SUM);
            mma16816(d0, f0[4], b2[0], b2[1]); mma16816(d1, f1[4], b2[0], b2[1]);
            mma16816(d0, f0[1], b2[2], b2[3]); mma16816(d1, f1[1], b2[2], b2[3]);
            mma16816(d0, f0[2], b0[0], b0[1]); mma16816(d1, f1[2], b0[0], b0[1]);
            mma16816(d0, f0[3], b0[2], b0[3]); mma16816(d1, f1[3], b0[2], b0[3]);
            const float r0 = rcp(sm[0]), r1 = rcp(sm[1]);
            const uint32_t w3 = (((l16 >> 6) ^ warp) & 1) ? 0x3F803F80u : pack2(d1[2] * r0, d1[3] * r1);
            asm volatile("red.relaxed.gpu.global.add.noftz.v4.bf16x2 [%0], {%1,%2,%3,%4};"
                         ::"l"(rp), "r"(pack2(d0[0] * r0, d0[1] * r1)), "r"(pack2(d0[2] * r0, d0[3] * r1)), "r"(pack2(d1[0] * r0, d1[1] * r1)), "r"(w3) : "memory");
            TS(3);
            bar_sync<NB_EPI, 256>();
        }
        rp += (s & 7) == 7 ? -7 * ACC_SLOT : ACC_SLOT;
    }
    bar_sync<NB_EPI, 256>();
    if (threadIdx.x == 160) {
        bulk_s2g(g_qkv + ((NSEG - 1) * NH + head) * QKV_ITEM + RANK * 2560, sb + (ISV ? R_VT + (NSEG - 1) % 3 * 10240 : R_QK + 10240), 10240);
        asm volatile("cp.async.bulk.wait_group 0;\n\tfence.proxy.async.global;" ::: "memory");
        red_add_gpu(&g_qready[NSEG - 1]);
    }
    __syncwarp();
}

__global__ void __launch_bounds__(384, 1)
rec_kernel(const __grid_constant__ CUtensorMap tmX, const __grid_constant__ CUtensorMap tmWq, const __grid_constant__ CUtensorMap tmWk,
           const __grid_constant__ CUtensorMap tmWv, const __grid_constant__ CUtensorMap tmWo, const bf16* __restrict__ mem0, const int poll_delay) {
    extern __shared__ uint8_t smem_raw[];
    const uint32_t sb = (smem_u32(smem_raw) + 1023) & ~1023u;
    uint32_t rank; asm volatile("mov.u32 %0, %%cluster_ctarank;" : "=r"(rank));
    const int head = blockIdx.x / 3;
    const uint32_t bars = sb + R_BAR;

    if (threadIdx.x == 0) {
        for (int i = 0; i < B_NUM; i++) mbar_init(bars + 8 * i, i == B_XF ? 12 : (i == B_S && rank < 2) ? 4 : 1);
        asm volatile("fence.mbarrier_init.release.cluster;" ::: "memory");
        fence_proxy_async();
        const CUtensorMap* mA = rank == 2 ? &tmWv : &tmWq;
        const CUtensorMap* mB = rank == 2 ? &tmWv : &tmWk;
        const int colA = head * 128 + (rank == 1 ? 64 : 0), colB = head * 128 + (rank == 0 ? 0 : 64);
        for (int q = 0; q < 4; q++) {
            mbar_expect(bars + 8 * (B_W0 + q), 40960);
            tma2d(sb + R_WST + q * 20480, mA, colA, q * 160, bars + 8 * (B_W0 + q));
            tma2d(sb + R_WST + (4 + q) * 20480, mB, colB, q * 160, bars + 8 * (B_W0 + q));
        }
        mbar_expect(bars + 8 * (B_X0 + 0), 40960);
        mbar_expect(bars + 8 * (B_X0 + 1), 40960);
    }
    asm volatile("griddepcontrol.launch_dependents;" ::: "memory");
    __syncthreads();
    cluster_sync_relaxed();
    if (threadIdx.x == 0) {
        if (rank < 2) tma3d_mc(sb + R_XB + rank * 20480, &tmX, 0, rank * 5, bars + 8 * B_X0, 7);
        for (int q = 0; q < 4; q++) tma2d_prefetch(&tmWo, rank * 224 + q * 64, head * 128);
    }
    __syncwarp();

    if (threadIdx.x < 256) {
        asm volatile("setmaxnreg.inc.sync.aligned.u32 224;");
        const int warp = __shfl_sync(~0u, threadIdx.x >> 5, 0), j = warp >> 2;
        uint32_t wk_[20][4], ws_[20][4];
        {
            const int lane = threadIdx.x & 31, w = warp & 3, m = lane >> 3, r8 = lane & 7;
            const uint32_t la = ((m >> 1) * 8 + r8) * 128 + (((2 * w + (m & 1)) ^ r8) << 4);
#pragma unroll
            for (int hlf = 0; hlf < 2; hlf++) {
                const int qk = rank == 2 ? hlf : 2 * j + hlf, qs = rank == 2 ? 2 + hlf : 2 * j + hlf;
                mbar_wait(bars + 8 * (B_W0 + qk), 0);
                mbar_wait(bars + 8 * (B_W0 + qs), 0);
                const uint32_t bk = sb + R_WST + (j * 4 + qk) * 20480 + la, bs = sb + R_WST + ((rank == 2 ? j : 1 - j) * 4 + qs) * 20480 + la;
#pragma unroll
                for (int k = 0; k < 10; k++) {
                    ldsm4t(wk_[hlf * 10 + k], bk + k * 2048);
                    ldsm4t(ws_[hlf * 10 + k], bs + k * 2048);
                }
            }
        }
        fence_proxy_async();
        cluster_sync_all();
        if (threadIdx.x == 0) {
            if (rank < 2) tma3d_mc(sb + R_XB + 40960 + rank * 20480, &tmX, SEG, rank * 5, bars + 8 * (B_X0 + 1), 7);
            mbar_expect(bars + 8 * B_WO, 65536);
            for (int q = 0; q < 4; q++) tma2d(sb + R_WO + q * 16384, &tmWo, rank * 224 + q * 64, head * 128, bars + 8 * B_WO);
        }
        __syncwarp();
        if (rank == 0) main_loop<0>(sb, head, warp, wk_, ws_, &tmX, poll_delay);
        else if (rank == 1) main_loop<1>(sb, head, warp, wk_, ws_, &tmX, poll_delay);
        else main_loop<2>(sb, head, warp, wk_, ws_, &tmX, poll_delay);
        cluster_sync_all();
    } else {
        asm volatile("setmaxnreg.dec.sync.aligned.u32 56;");
        if (threadIdx.x >= 352) { asm volatile("st.shared.u32 [%0], %1;" ::"r"(sb + R_ZERO + (threadIdx.x & 31) * 4), "r"(0) : "memory"); fence_proxy_async(); }
        if (threadIdx.x < 256 + 32) {
            g_acc[((threadIdx.x - 256) >> 3) * ACC_SLOT + blockIdx.x * ACC_LINE + (threadIdx.x & 7)] = make_uint4(0, 0, 0, 0);
            fence_release_gpu();
            __syncwarp();
            if ((threadIdx.x & 31) == 0) red_add_gpu(&g_start);
        }
        cluster_sync_all();
        for (int i = threadIdx.x - 256; i < DM * 4; i += 128) {
            const int col = i >> 2, rp = i & 3;
            const uint32_t lo = __bfloat16_as_ushort(mem0[(2 * rp) * DM + col]), hi = __bfloat16_as_ushort(mem0[(2 * rp + 1) * DM + col]);
            asm volatile("st.shared.u32 [%0], %1;" ::"r"(sb + R_MEM + i * 4), "r"(lo | (hi << 16)) : "memory");
        }
        if (threadIdx.x == 256) {
            unsigned v; int lim = 0;
            do { asm volatile("ld.acquire.gpu.global.u32 %0, [%1];" : "=r"(v) : "l"(&g_start) : "memory"); if (++lim > (1 << 22)) __trap(); } while (v < 96);
        }
        __syncwarp();
        if (rank == 0) aux_loop<0>(sb, head, &tmX, poll_delay);
        else if (rank == 1) aux_loop<1>(sb, head, &tmX, poll_delay);
        else aux_loop<2>(sb, head, &tmX, poll_delay);
        __syncwarp();
        cluster_sync_all();
    }
}

constexpr int G_STAGES = 4, G_STAGE = 49152;
constexpr int A_STAGES = 7, A_STAGE = 30720;
constexpr int G_BAR = A_STAGES * A_STAGE;
constexpr int G_SMEM = G_BAR + 512 + 1024;
#define N_ATT 8
#define TASK_ORDER "H0H1P0H2P1H3P2H4O00P3H5O10P4H6P5H7O20P6P7O31O41Z00wa2Z10wb2wc2Z31wd3Z20Z41za2we3df4zb2zc2zd3ze3"
enum { T_EXIT = 0, T_H = 1, T_F = 2, T_Z = 3, T_A = 3 };
enum { C_QA = 0, C_QO = 32, C_QP = 64, C_QH = 96, C_DONE = 128, C_GATE = 144, C_HREADY = 160, C_OREADY = 192, C_PDONE = 224, C_FCNT = 288, C_NUM = 384 };
__device__ unsigned g_cnt[C_NUM];
#define TL(i)
__device__ float g_gate[S_TOK];
__device__ __align__(1024) float4 g_ws2[160 * 4096];
__device__ __align__(1024) float4 g_ws[80 * 4096];
constexpr int N_QA = 512;

__device__ __forceinline__ unsigned ld_relaxed(const unsigned* p) { unsigned v; asm volatile("ld.relaxed.gpu.global.u32 %0, [%1];" : "=r"(v) : "l"(p) : "memory"); return v; }
__device__ __forceinline__ unsigned ld_acquire(const unsigned* p) { unsigned v; asm volatile("ld.acquire.gpu.global.u32 %0, [%1];" : "=r"(v) : "l"(p) : "memory"); return v; }
__device__ __forceinline__ void bulk_g2s(uint32_t dst, const void* src, int bytes, uint32_t bar) {
    asm volatile("cp.async.bulk.shared::cluster.global.mbarrier::complete_tx::bytes [%0], [%1], %2, [%3];" ::"r"(dst), "l"(src), "r"(bytes), "r"(bar) : "memory");
}
__device__ __forceinline__ void mbar_wait1(uint32_t b, int par) {
    uint32_t ok; int lim = 0;
    while (true) {
        asm volatile("{.reg .pred p; mbarrier.try_wait.parity.shared::cta.b64 p, [%1], %2; selp.u32 %0, 1, 0, p;}" : "=r"(ok) : "r"(b), "r"(par) : "memory");
        if (ok) break;
        if (++lim > (1 << 22)) __trap();
    }
}
__device__ __forceinline__ void wgmma_n128(float* d, uint64_t da, uint64_t db, int acc) {
    asm volatile("{\n\t.reg .pred p;\n\tsetp.ne.s32 p, %66, 0;\n\t"
                 "wgmma.mma_async.sync.aligned.m64n128k16.f32.bf16.bf16 {%0,%1,%2,%3,%4,%5,%6,%7,%8,%9,%10,%11,%12,%13,%14,%15,%16,%17,%18,%19,%20,%21,%22,%23,%24,%25,%26,%27,%28,%29,%30,%31,"
                 "%32,%33,%34,%35,%36,%37,%38,%39,%40,%41,%42,%43,%44,%45,%46,%47,%48,%49,%50,%51,%52,%53,%54,%55,%56,%57,%58,%59,%60,%61,%62,%63}, %64, %65, p, 1, 1, 0, 1;\n\t}"
                 : "+f"(d[0]), "+f"(d[1]), "+f"(d[2]), "+f"(d[3]), "+f"(d[4]), "+f"(d[5]), "+f"(d[6]), "+f"(d[7]), "+f"(d[8]), "+f"(d[9]), "+f"(d[10]), "+f"(d[11]),
                   "+f"(d[12]), "+f"(d[13]), "+f"(d[14]), "+f"(d[15]), "+f"(d[16]), "+f"(d[17]), "+f"(d[18]), "+f"(d[19]), "+f"(d[20]), "+f"(d[21]), "+f"(d[22]), "+f"(d[23]),
                   "+f"(d[24]), "+f"(d[25]), "+f"(d[26]), "+f"(d[27]), "+f"(d[28]), "+f"(d[29]), "+f"(d[30]), "+f"(d[31]), "+f"(d[32]), "+f"(d[33]), "+f"(d[34]), "+f"(d[35]),
                   "+f"(d[36]), "+f"(d[37]), "+f"(d[38]), "+f"(d[39]), "+f"(d[40]), "+f"(d[41]), "+f"(d[42]), "+f"(d[43]), "+f"(d[44]), "+f"(d[45]), "+f"(d[46]), "+f"(d[47]),
                   "+f"(d[48]), "+f"(d[49]), "+f"(d[50]), "+f"(d[51]), "+f"(d[52]), "+f"(d[53]), "+f"(d[54]), "+f"(d[55]), "+f"(d[56]), "+f"(d[57]), "+f"(d[58]), "+f"(d[59]),
                   "+f"(d[60]), "+f"(d[61]), "+f"(d[62]), "+f"(d[63])
                 : "l"(da), "l"(db), "r"(acc));
}
struct TaskList { int n; int t[640]; };
constexpr TaskList make_tasks() {
    TaskList L{};
    const char* order = TASK_ORDER;
    for (int i = 0; order[i];) {
        const char c = order[i];
        const int b = order[i + 1] <= '9' ? order[i + 1] - '0' : order[i + 1] - 'a' + 10;
        if (c == 'H') { for (int k = 0; k < KC_H; k++) L.t[L.n++] = T_H | (2 * b << 2) | (1 << 6) | (k << 7) | (10 << 19); i += 2; }
        else if (c == 'P') { for (int k = 0; k < 5; k++) L.t[L.n++] = T_F | (2 * b << 2) | (1 << 6) | (k << 7) | (KC_O << 12) | (KC_H << 19); i += 2; }
        else if (c == 'Z' || c == 'z') {
            const int lg = order[i + 2] - '0';
            for (int h = 0; h < (c == 'Z' ? 2 : 1); h++)
                for (int k = 0; k < 5; k++) {
                    const int tb = c == 'Z' ? 2 * b + h : b, ctr = c == 'Z' ? 2 * b * 5 + k : b * 5 + (k & 6);
                    L.t[L.n++] = T_Z | (tb << 2) | (k << 7) | (ctr << 12) | ((c == 'z' && k == 4 ? 1 << (lg - 1) : 1 << lg) << 19);
                }
            i += 3;
        }
        else {
            const int lg = order[i + 2] - '0';
            const int ks = ((64 >> lg) << 19) | ((lg + 1) << 26);
            if (c == 'O') {
                for (int sp = 0; sp < (1 << lg); sp++)
                    for (int k = 0; k < 5; k++) L.t[L.n++] = T_F | (2 * b << 2) | (1 << 6) | (k << 7) | ((sp * (64 >> lg)) << 12) | ks;
            } else if (c == 'w') {
                for (int sp = 0; sp < (1 << lg); sp++) {
                    for (int k = 0; k < 4; k += 2) L.t[L.n++] = T_F | (b << 2) | (1 << 6) | (k << 7) | ((sp * (64 >> lg)) << 12) | ks | (1 << 30);
                    if (!(sp & 1)) L.t[L.n++] = T_F | (b << 2) | (4 << 7) | ((sp * (64 >> lg)) << 12) | ((128 >> lg) << 19) | (lg << 26);
                }
            } else {
                for (int k = 0; k < 5; k++)
                    for (int sp = 0; sp < (1 << lg); sp++) L.t[L.n++] = T_F | (b << 2) | (k << 7) | ((sp * (64 >> lg)) << 12) | ks | (1 << 29);
            }
            i += 3;
        }
    }
    return L;
}
__device__ const TaskList g_tasks = make_tasks();

__device__ __forceinline__ void attention_item(const uint32_t base, const int item, const int m, const int lane) {
    const float SC = 0.08838834764831845f * 1.4426950408889634f;
    const int mi = lane >> 3, g = lane >> 2, c = lane & 3;
    const uint32_t l16 = base + lane * 16;
    const uint32_t qa = base + (2 * m + (mi & 1)) * 256 + (mi >> 1) * 128 + (lane & 7) * 16;
    float sv[6][4];
#pragma unroll
    for (int i = 0; i < 6; i++)
#pragma unroll
        for (int e = 0; e < 4; e++) sv[i][e] = 0.f;
#pragma unroll
    for (int ks = 0; ks < 8; ks++) {
        const int ho = (ks >> 2) * 10240, k4 = ks & 3;
        uint32_t qf[4], k0[4], k1[4], km[4];
        ldsm4t(qf, qa + ho + k4 * 1024); ldsm4t(k0, l16 + ho + 4096 + k4 * 1024); ldsm4t(km, l16 + ho + 8192 + k4 * 512);
        mma16816(sv[0], qf, k0[0], k0[1]); mma16816(sv[1], qf, k0[2], k0[3]);
        mma16816(sv[4], qf, km[0], km[1]); mma16816(sv[5], qf, km[2], km[3]);
        if (m) { ldsm4t(k1, l16 + ho + 4096 + k4 * 1024 + 512); mma16816(sv[2], qf, k1[0], k1[1]); mma16816(sv[3], qf, k1[2], k1[3]); }
    }
#pragma unroll
    for (int e = 0; e < 4; e++) sv[4][e] += sv[5][e];
#pragma unroll
    for (int i = 0; i < 4; i++)
#pragma unroll
        for (int e = 0; e < 4; e++)
            if (8 * i + (e & 1) - (e >> 1) * 8 > 16 * m + g - 2 * c) sv[i][e] = -INFINITY;
    float mx0 = fmaxf(sv[4][0], sv[4][1]), mx1 = fmaxf(sv[4][2], sv[4][3]);
#pragma unroll
    for (int i = 0; i < 4; i++) { mx0 = fmaxf(mx0, fmaxf(sv[i][0], sv[i][1])); mx1 = fmaxf(mx1, fmaxf(sv[i][2], sv[i][3])); }
    mx0 = fmaxf(mx0, __shfl_xor_sync(~0u, mx0, 1)); mx1 = fmaxf(mx1, __shfl_xor_sync(~0u, mx1, 1));
    mx0 = fmaxf(mx0, __shfl_xor_sync(~0u, mx0, 2)); mx1 = fmaxf(mx1, __shfl_xor_sync(~0u, mx1, 2));
    mx0 *= -SC; mx1 *= -SC;
    float sum0 = 0.f, sum1 = 0.f;
#pragma unroll
    for (int i = 0; i < 5; i++) {
        sv[i][0] = ex2(fmaf(sv[i][0], SC, mx0)); sv[i][1] = ex2(fmaf(sv[i][1], SC, mx0));
        sv[i][2] = ex2(fmaf(sv[i][2], SC, mx1)); sv[i][3] = ex2(fmaf(sv[i][3], SC, mx1));
        sum0 += sv[i][0] + sv[i][1]; sum1 += sv[i][2] + sv[i][3];
    }
    sum0 += __shfl_xor_sync(~0u, sum0, 1); sum1 += __shfl_xor_sync(~0u, sum1, 1);
    sum0 += __shfl_xor_sync(~0u, sum0, 2); sum1 += __shfl_xor_sync(~0u, sum1, 2);
    const float r0 = rcp(sum0), r1 = rcp(sum1);
    uint32_t pa[10];
#pragma unroll
    for (int i = 0; i < 5; i++) { pa[2 * i] = pack2(sv[i][0] * r0, sv[i][1] * r0); pa[2 * i + 1] = pack2(sv[i][2] * r1, sv[i][3] * r1); }
    const int seg = item >> 5, head = item & 31;
    uint32_t* og = g_act + (((seg >> 2) * KC_ALL + 2 * head) * 16 + (seg & 3) * 4 + 2 * m) * 256 + lane;
#pragma unroll
    for (int n4 = 0; n4 < 4; n4++) {
        uint32_t vm[4], vf[4][4];
        float o[4][4];
        ldsm4(vm, l16 + 28672 + n4 * 512);
#pragma unroll
        for (int q = 0; q < 4; q++) ldsm4(vf[q], l16 + 20480 + (n4 * 4 + q) * 512);
#pragma unroll
        for (int q = 0; q < 4; q++) mma1688z(o[q], pa[8], pa[9], vm[q]);
#pragma unroll
        for (int q = 0; q < 4; q++) mma16816(o[q], pa, vf[q][0], vf[q][1]);
        if (m) {
#pragma unroll
            for (int q = 0; q < 4; q++) mma16816(o[q], pa + 4, vf[q][2], vf[q][3]);
        }
#pragma unroll
        for (int q = 0; q < 4; q++) {
            const int n = n4 * 4 + q;
            og[(n >> 3) * 4096 + (n & 7) * 32] = pack2(o[q][0], o[q][1]);
            og[(n >> 3) * 4096 + (n & 7) * 32 + 256] = pack2(o[q][2], o[q][3]);
        }
    }
}

__global__ void __launch_bounds__(384, 1)
gemm_kernel(const __grid_constant__ CUtensorMap tmX, const __grid_constant__ CUtensorMap tmWg, const __grid_constant__ CUtensorMap tmWu,
            const __grid_constant__ CUtensorMap tmWo, const __grid_constant__ CUtensorMap tmWd, const bf16* __restrict__ x, const bf16* __restrict__ gw,
            bf16* __restrict__ out) {
    extern __shared__ uint8_t smem_raw[];
    const uint32_t sb = (smem_u32(smem_raw) + 1023) & ~1023u;
    const uint32_t full = sb + G_BAR, empty = full + 32, afull = full + 64, aempty = afull + 56, bwant = aempty + 56, bready = bwant + 8;
    const uint32_t sfull = bready + 8, sempty = sfull + 32, info = sempty + 32, ainfo = info + 16, mail = ainfo + 32, sinfo = mail + 4, sflag = sinfo + 16;
    const int tid = threadIdx.x, warp = __shfl_sync(~0u, tid >> 5, 0), lane = tid & 31;
    const bool att = blockIdx.x < N_ATT || (blockIdx.x >= 36 && blockIdx.x < 68);
    if (tid == 0) {
        for (int i = 0; i < G_STAGES; i++) { mbar_init(full + 8 * i, 1); mbar_init(empty + 8 * i, 2); mbar_init(sfull + 8 * i, 8); mbar_init(sempty + 8 * i, 1); }
        for (int i = 0; i < A_STAGES; i++) { mbar_init(afull + 8 * i, 1); mbar_init(aempty + 8 * i, 2); }
        mbar_init(bwant, 1); mbar_init(bready, 1);
        fence_proxy_async();
    }
    __syncthreads();

    if (warp >= 8) {
        asm volatile("setmaxnreg.dec.sync.aligned.u32 40;");
        if (warp == 8 && lane == 0) {
            if (att) {
                int st = 0, ph = 1, idle = 0, okseg = -1, seq = 0;
                int tn = atomicAdd(g_cnt + C_QA, 1);
                while (true) {
                    const int t = tn;
                    const int seg = t >> 3;
                    if (t < N_QA && seg > okseg) {
                        while (ld_acquire(g_qready + seg) != 96) { __nanosleep(50); if (++idle > (1 << 22)) __trap(); }
                        okseg = seg;
                        if (seg == 63) TL(7);
                        asm volatile("fence.proxy.async.global;" ::: "memory");
                    }
                    if (t < N_QA) tn = atomicAdd(g_cnt + C_QA, 1);
                    for (int k = 0; k < 4; k++) {
                        mbar_wait1(aempty + 8 * st, ph);
                        asm volatile("st.shared.u32 [%0], %1;" ::"r"(ainfo + 4 * st), "r"((t < N_QA ? t * 4 + k : 2048) | (++seq << 12)) : "memory");
                        if (t < N_QA) {
                            mbar_expect(afull + 8 * st, A_STAGE);
                            asm volatile("{\n\t.reg .b64 pol;\n\tcreatepolicy.fractional.L2::evict_first.b64 pol, 1.0;\n\t"
                                         "cp.async.bulk.shared::cluster.global.mbarrier::complete_tx::bytes.L2::cache_hint [%0], [%1], %2, [%3], pol;\n\t}"
                                         ::"r"(sb + st * A_STAGE), "l"(g_qkv + (size_t)(t * 4 + k) * QKV_ITEM), "r"(A_STAGE), "r"(afull + 8 * st) : "memory");
                        } else {
                            mbar_arrive(afull + 8 * st);
                        }
                        if (++st == A_STAGES) { st = 0; ph ^= 1; }
                    }
                    if (t >= N_QA) break;
                }
                for (int k = 0; k < A_STAGES; k++) {
                    mbar_wait1(aempty + 8 * st, ph);
                    if (++st == A_STAGES) { st = 0; ph ^= 1; }
                }
            }
            int st = 0, ph = 1, mp = 0;
            auto next = [&]() { if (++st == G_STAGES) { st = 0; ph ^= 1; } };
            mbar_arrive(bwant);
            while (true) {
                mbar_wait1(bready, mp); mp ^= 1;
                int task; asm volatile("ld.shared.u32 %0, [%1];" : "=r"(task) : "r"(mail) : "memory");
                asm volatile("fence.proxy.async.global;" ::: "memory");
                const int type = task & 3, tb = (task >> 2) & 15, big = (task >> 6) & 1;
                const int nt = (task >> 7) & 31, k0 = (task >> 12) & 127, nk = (task >> 19) & 127, wide = (task >> 30) & 1;
                mbar_wait1(empty + 8 * st, ph);
                asm volatile("st.shared.u32 [%0], %1;" ::"r"(info + 4 * st), "r"(task) : "memory");
                if (type == T_EXIT) { mbar_arrive(full + 8 * st); break; }
                if (type == T_Z) {
                    mbar_arrive(bwant);
                    for (int k = 0; k < 2; k++) {
                        if (k) mbar_wait1(empty + 8 * st, ph);
                        mbar_expect(full + 8 * st, 32768);
                        bulk_g2s(sb + st * G_STAGE, g_ws + (tb * 5 + nt) * 4096 + k * 2048, 32768, full + 8 * st);
                        next();
                    }
                    continue;
                }
                const CUtensorMap* mw = k0 >= KC_O ? &tmWd : &tmWo;
                if (task & (1 << 29)) {
                    for (int k = 0; k < G_STAGES; k++) {
                        if (k) mbar_wait1(empty + 8 * st, ph);
                        mbar_expect(full + 8 * st, 32768);
                        tma2d(sb + st * G_STAGE + 32768, mw, nt * 128, (k0 + k) * 64, full + 8 * st);
                        tma2d(sb + st * G_STAGE + 40960, mw, nt * 128 + 64, (k0 + k) * 64, full + 8 * st);
                        next();
                    }
                    for (int part = 0; part < 2; part++) {
                        int lim = 0;
                        while (ld_acquire(g_cnt + C_OREADY + tb + part) < (part ? 8 : 24)) { __nanosleep(40); if (++lim > (1 << 22)) __trap(); }
                        asm volatile("fence.proxy.async.global;" ::: "memory");
                        for (int k = 0; k < G_STAGES; k++) {
                            const int s2 = (st + k) & (G_STAGES - 1);
                            bulk_g2s(sb + s2 * G_STAGE + part * 12288, g_act + (tb * KC_ALL + k0 + k) * 4096 + part * 3072, part ? 4096 : 12288, full + 8 * s2);
                        }
                    }
                    TL(0);
                    continue;
                }
                for (int k = 0; k < nk; k++) {
                    if (k == (nk > 4 ? nk - 4 : 0)) {
                        if (!(task >> 26) || tb < 12) mbar_arrive(bwant);
                        if (task >> 26)
                            for (int i = 0; i < 4 + 4 * big; i++)
                                asm volatile("cp.async.bulk.prefetch.L2.global [%0], %1;" ::"l"(g_ws + (tb * 5 + nt + (i >> 2) * (wide ? 1 : 5)) * 4096 + (i & 3) * 1024), "r"(16384) : "memory");
                    }
                    if (k) mbar_wait1(empty + 8 * st, ph);
                    const uint32_t d = sb + st * G_STAGE, b = full + 8 * st;
                    mbar_expect(b, big ? 49152 : 32768);
                    if (type == T_H) {
                        tma2d(d, &tmX, k * 64, tb * 128, b);
                        tma2d(d + 32768, &tmWg, nt * 64, k * 64, b);
                        tma2d(d + 40960, &tmWu, nt * 64, k * 64, b);
                    } else {
                        const int kc = k0 + k, row = (kc >= KC_O ? kc - KC_O : kc) * 64;
                        bulk_g2s(d, g_act + (tb * KC_ALL + kc) * 4096, 16384, b);
                        if (wide) { tma2d(d + 16384, mw, nt * 128 + 128, row, b); tma2d(d + 24576, mw, nt * 128 + 192, row, b); }
                        else if (big) bulk_g2s(d + 16384, g_act + ((tb + 1) * KC_ALL + kc) * 4096, 16384, b);
                        tma2d(d + 32768, mw, nt * 128, row, b);
                        tma2d(d + 40960, mw, nt * 128 + 64, row, b);
                    }
                    next();
                }
            }
        } else if (warp == 9 && lane == 0) {
            int idle = 0, wp = 0;
            auto await = [&](int ctr, unsigned v) { while (ld_acquire(g_cnt + ctr) < v) { __nanosleep(50); if (++idle > (1 << 22)) __trap(); } };
            while (true) {
                mbar_wait1(bwant, wp); wp ^= 1;
                const unsigned i = atomicAdd(g_cnt + C_QH, 1);
                const int task = i < (unsigned)g_tasks.n ? g_tasks.t[i] : T_EXIT;
                if ((task & 3) == T_Z) await(C_FCNT + ((task >> 12) & 127), (task >> 19) & 127);
                if ((task & 3) == T_F) {
                    const int tb = (task >> 2) & 15;
                    if ((task >> 26) == 0) { await(C_GATE, N_ATT); await(C_HREADY + (tb >> 1), KC_H); }
                    else {
                        await(C_PDONE + (tb >> 1) * 5 + ((task >> 7) & 7), 1);
                        if (task >> 30) await(C_PDONE + (tb >> 1) * 5 + ((task >> 7) & 7) + 1, 1);
                        if (!(task & (1 << 29))) await(C_OREADY + tb, 32);
                        if ((task & 64) && !(task >> 30)) await(C_OREADY + tb + 1, 32);
                    }
                }
                asm volatile("st.shared.u32 [%0], %1;" ::"r"(mail), "r"(task) : "memory");
                mbar_arrive(bready);
                if (task == T_EXIT) break;
            }
        } else if (warp == 10 && lane == 0) {
            for (int n = 0;; n++) {
                mbar_wait1(sfull + 8 * (n & 3), (n >> 2) & 1);
                int c; asm volatile("ld.shared.u32 %0, [%1];" : "=r"(c) : "r"(sinfo + 4 * (n & 3)) : "memory");
                mbar_arrive(sempty + 8 * (n & 3));
                if (c < 0) break;
                asm volatile("fence.proxy.async.global;" ::: "memory");
                if (c == C_OREADY + 16) TL(5);
                fence_release_gpu();
                red_add_gpu(g_cnt + c);
                if (c == C_OREADY + 16) TL(6);
            }
        }
    } else {
        asm volatile("setmaxnreg.inc.sync.aligned.u32 232;");
        const int wg = warp >> 2, g = lane >> 2, c = lane & 3;
        int nsig = 0, nlog = 0;
        auto signal = [&](int ctr) {
            mbar_wait(sempty + 8 * (nsig & 3), ((nsig >> 2) & 1) ^ 1);
            __syncwarp();
            if (lane == 0) {
                if (warp == 0) asm volatile("st.shared.u32 [%0], %1;" ::"r"(sinfo + 4 * (nsig & 3)), "r"(ctr) : "memory");
                mbar_arrive(sfull + 8 * (nsig & 3));
            }
            nsig++;
        };
        if (blockIdx.x < N_ATT) {
            float wv[20];
#pragma unroll
            for (int i = 0; i < 10; i++) { const uint32_t u = ((const uint32_t*)gw)[i * 32 + lane]; wv[2 * i] = __uint_as_float(u << 16); wv[2 * i + 1] = __uint_as_float(u & 0xFFFF0000u); }
#pragma unroll 1
            for (int r0 = (blockIdx.x * 8 + warp) * 8; r0 < S_TOK; r0 += N_ATT * 64) {
                uint32_t u[8][10];
#pragma unroll
                for (int r = 0; r < 8; r++)
#pragma unroll
                    for (int i = 0; i < 10; i++) u[r][i] = __ldg((const uint32_t*)x + (r0 + r) * (DM / 2) + i * 32 + lane);
                float mine = 0.f;
#pragma unroll
                for (int r = 0; r < 8; r++) {
                    float a = 0.f;
#pragma unroll
                    for (int i = 0; i < 10; i++) { a = fmaf(__uint_as_float(u[r][i] << 16), wv[2 * i], a); a = fmaf(__uint_as_float(u[r][i] & 0xFFFF0000u), wv[2 * i + 1], a); }
#pragma unroll
                    for (int o = 16; o; o >>= 1) a += __shfl_xor_sync(~0u, a, o);
                    if (lane == r) mine = a;
                }
                if (lane < 8) g_gate[r0 + lane] = 1.f / (1.f + __expf(-mine));
            }
            signal(C_GATE);
        }
        if (att) {
            int st = warp >> 1, ph = 0, seq = st + 1;
            while (true) {
                int item, lim = 0;
                do {
                    mbar_wait(afull + 8 * st, ph);
                    asm volatile("ld.volatile.shared.u32 %0, [%1];" : "=r"(item) : "r"(ainfo + 4 * st) : "memory");
                    item = __shfl_sync(~0u, item, 0);
                    if (++lim > (1 << 22)) __trap();
                } while ((item >> 12) != seq);
                seq += 4;
                item = (item & 2048) ? -1 : item & 2047;
                if (item >= 0) attention_item(sb + st * A_STAGE, item, (warp ^ (seq >> 2)) & 1, lane);
                __syncwarp();
                if (lane == 0) mbar_arrive(aempty + 8 * st);
                if (item < 0) break;
                signal(C_OREADY + (item >> 7) + (item >= (NSEG - 1) * NH));
                st += 4; if (st >= A_STAGES) { st -= A_STAGES; ph ^= 1; }
            }
        }
        int st = 0, ph = 0;
        auto next = [&]() { if (++st == G_STAGES) { st = 0; ph ^= 1; } };
        while (true) {
            mbar_wait(full + 8 * st, ph);
            int task; asm volatile("ld.shared.u32 %0, [%1];" : "=r"(task) : "r"(info + 4 * st) : "memory");
            task = __shfl_sync(~0u, task, 0);
            const int type = task & 3, tb = (task >> 2) & 15, big = (task >> 6) & 1, nt = (task >> 7) & 31, nk = type == T_Z ? 0 : (task >> 19) & 127;
            if (type == T_EXIT) { signal(-1); break; }
            if (type == T_Z) {
#pragma unroll 1
                for (int k = 0; k < 2; k++) {
                    if (k) mbar_wait(full + 8 * st, ph);
                    float v[8][4];
#pragma unroll
                    for (int i = 0; i < 8; i++) lds128f(v[i], sb + st * G_STAGE + g * 4096 + (i * 8 + warp) * 64 + c * 16);
                    uint32_t* og = (uint32_t*)out + (tb * 128 + warp) * (DM / 2) + nt * 64 + k * 32 + lane;
#pragma unroll
                    for (int i = 0; i < 8; i++) { og[i * 16 * (DM / 2)] = pack2(v[i][0], v[i][1]); og[(i * 16 + 8) * (DM / 2)] = pack2(v[i][2], v[i][3]); }
                    bar_sync_r(2 + wg, 128);
                    if ((tid & 127) == 0) mbar_arrive(empty + 8 * st);
                    next();
                }
                continue;
            }
            const uint64_t ahi = type == T_H ? ((1ull << 16) | (64ull << 32) | (1ull << 62)) : ((8ull << 16) | (64ull << 32));
            const uint32_t astep = type == T_H ? 2 : 16;
            const uint64_t bhi = (512ull << 16) | (64ull << 32) | (1ull << 62);
            const int wide = (task >> 30) & 1;
            const uint32_t a2 = wide ? 0 : 1024, b2 = wide ? 1024 : 0;
            float acc[2][64];
#pragma unroll
            for (int i = 0; i < 64; i++) { acc[0][i] = 0.f; acc[1][i] = 0.f; }
            int pst = st;
            if (big) {
#pragma unroll 1
                for (int k = 0; k < nk; k++) {
                    if (k) mbar_wait(full + 8 * st, ph);
                    const uint32_t d = sb + st * G_STAGE;
                    const uint64_t da = ahi | (uint64_t)(((d + wg * 8192) & 0x3FFFF) >> 4), db = bhi | (uint64_t)(((d + 32768) & 0x3FFFF) >> 4);
                    WG_FENCE();
#pragma unroll
                    for (int q = 0; q < 4; q++) { wgmma_n128(acc[0], da + q * astep, db + q * 128, 1); wgmma_n128(acc[1], da + a2 + q * astep, db - b2 + q * 128, 1); }
                    WG_COMMIT();
                    if (k) {
                        asm volatile("wgmma.wait_group.sync.aligned 1;" ::: "memory");
                        bar_sync_r(2 + wg, 128);
                        if ((tid & 127) == 0) mbar_arrive(empty + 8 * pst);
                    }
                    pst = st;
                    next();
                }
                WG_WAIT0();
            } else {
#pragma unroll 1
                for (int k = 0; k < nk; k++) {
                    if (k) mbar_wait(full + 8 * st, ph);
                    const uint32_t d = sb + st * G_STAGE;
                    const uint64_t da = ahi | (uint64_t)(((d + wg * 8192) & 0x3FFFF) >> 4), db = bhi | (uint64_t)(((d + 32768) & 0x3FFFF) >> 4);
                    WG_FENCE();
#pragma unroll
                    for (int q = 0; q < 4; q++) wgmma_n128(acc[0], da + q * astep, db + q * 128, 1);
                    WG_COMMIT();
                    if (k) {
                        asm volatile("wgmma.wait_group.sync.aligned 1;" ::: "memory");
                        bar_sync_r(2 + wg, 128);
                        if ((tid & 127) == 0) mbar_arrive(empty + 8 * pst);
                    }
                    pst = st;
                    next();
                }
                WG_WAIT0();
            }
            bar_sync_r(2 + wg, 128);
            if ((tid & 127) == 0) mbar_arrive(empty + 8 * pst);
#pragma unroll
            for (int h = 0; h < 2; h++) { KEEP16(acc[h]); KEEP16((acc[h] + 16)); KEEP16((acc[h] + 32)); KEEP16((acc[h] + 48)); }
            if (type == T_H) {
#pragma unroll
                for (int h = 0; h < 2; h++) {
                    uint32_t* hg = g_act + (((tb + h) * KC_ALL + KC_O + nt) * 16 + warp * 2) * 256 + lane;
#pragma unroll
                    for (int n = 0; n < 8; n++) {
                        hg[n * 32] = pack2(acc[h][4 * n] * acc[h][32 + 4 * n], acc[h][4 * n + 1] * acc[h][33 + 4 * n]);
                        hg[256 + n * 32] = pack2(acc[h][4 * n + 2] * acc[h][34 + 4 * n], acc[h][4 * n + 3] * acc[h][35 + 4 * n]);
                    }
                }
                signal(C_HREADY + (tb >> 1));
            } else {
                const int mode = (task >> 26) & 7, hr = wide ? 0 : 1, hc = wide;
                if (task & (1 << 29)) {
                    if (tid == 0) TL(1);
                    const int S = 1 << (mode - 1), sp = ((task >> 12) & 127) / nk, row = tb * 128 + warp * 16 + g;
                    const float g0 = __ldcg(g_gate + row), g1 = __ldcg(g_gate + row + 8);
                    float4* w2 = g_ws2 + ((tb & 1) * 5 + nt) * 16 * 4096 + tid;
#pragma unroll
                    for (int n = 0; n < 16; n++) __stcg(w2 + sp * 4096 + n * 256, make_float4(acc[0][4 * n] * g0, acc[0][4 * n + 1] * g0, acc[0][4 * n + 2] * g1, acc[0][4 * n + 3] * g1));
                    const int so = (tid >> 2 & 15) * 256 + sp * 16 + (tid >> 6) * 4 + c;
                    float4 v = __ldcg(g_ws + (tb * 5 + nt) * 4096 + so);
                    bar_sync<1, 256>();
                    if (tid == 0) {
                        TL(2);
                        fence_release_gpu();
                        TL(3);
                        red_add_gpu(g_cnt + C_FCNT + tb * 5 + nt);
                        int lim = 0;
                        while (ld_acquire(g_cnt + C_FCNT + tb * 5 + nt) < S) if (++lim > (1 << 22)) __trap();
                        TL(4);
                    }
                    bar_sync<1, 256>();
                    float4 u[16];
#pragma unroll
                    for (int i = 0; i < 16; i++) u[i] = __ldcg(w2 - tid + i * 4096 + so);
#pragma unroll
                    for (int i = 0; i < 16; i++) { v.x += u[i].x; v.y += u[i].y; v.z += u[i].z; v.w += u[i].w; }
                    uint32_t* og = (uint32_t*)out + (tb * 128 + (sp >> 1) * 16 + (sp & 1) * 4 + (tid >> 6)) * (DM / 2) + nt * 64 + (tid & 63);
                    og[0] = pack2(v.x, v.y); og[8 * (DM / 2)] = pack2(v.z, v.w);
                } else {
#pragma unroll
                    for (int h = 0; h < 2; h++) {
                        if (h <= big) {
                            const int row = (tb + h * hr) * 128 + warp * 16 + g;
                            float g0 = __ldcg(g_gate + row), g1 = __ldcg(g_gate + row + 8);
                            float4* ws = g_ws + ((tb + h * hr) * 5 + nt + h * hc) * 4096 + tid;
                            if (mode == 0) {
                                g0 = 1.f - g0; g1 = 1.f - g1;
#pragma unroll
                                for (int n = 0; n < 16; n++) __stcg(ws + n * 256, make_float4(acc[h][4 * n] * g0, acc[h][4 * n + 1] * g0, acc[h][4 * n + 2] * g1, acc[h][4 * n + 3] * g1));
                            } else {
#pragma unroll
                                for (int n = 0; n < 16; n++)
                                    asm volatile("red.relaxed.gpu.global.add.v4.f32 [%0], {%1,%2,%3,%4};" ::"l"(ws + n * 256), "f"(acc[h][4 * n] * g0), "f"(acc[h][4 * n + 1] * g0),
                                                 "f"(acc[h][4 * n + 2] * g1), "f"(acc[h][4 * n + 3] * g1) : "memory");
                            }
                        }
                    }
                    signal(mode == 0 ? C_PDONE + (tb >> 1) * 5 + nt : C_FCNT + tb * 5 + nt);
                }
            }
            if ((task >> 26) && tb >= 12 && tid == 0) mbar_arrive(bwant);
        }
        bar_sync<1, 256>();
        if (warp == 0) {
            unsigned last = 0;
            if (lane == 0) {
                mbar_wait1(sempty + 8 * ((nsig - 1) & 3), ((nsig - 1) >> 2) & 1);
                asm volatile("griddepcontrol.wait;" ::: "memory");
                fence_release_gpu();
                last = atomicAdd(g_cnt + C_DONE, 1) == gridDim.x - 1;
            }
            if (__shfl_sync(~0u, last, 0)) {
                for (int i = lane; i < C_NUM; i += 32) g_cnt[i] = 0;
                g_qready[lane] = 0; g_qready[lane + 32] = 0;
            }
        }
    }
}

typedef CUresult (*EncodeFn)(CUtensorMap*, CUtensorMapDataType, cuuint32_t, void*, const cuuint64_t*, const cuuint64_t*, const cuuint32_t*,
                             const cuuint32_t*, CUtensorMapInterleave, CUtensorMapSwizzle, CUtensorMapL2promotion, CUtensorMapFloatOOBfill);
static void make_map(EncodeFn enc, CUtensorMap* m, const void* p, uint64_t cols, uint64_t rows, uint32_t bc, uint32_t br) {
    cuuint64_t dims[2] = {cols, rows}, strides[1] = {cols * 2};
    cuuint32_t box[2] = {bc, br}, es[2] = {1, 1};
    enc(m, CU_TENSOR_MAP_DATA_TYPE_BFLOAT16, 2, (void*)p, dims, strides, box, es, CU_TENSOR_MAP_INTERLEAVE_NONE, CU_TENSOR_MAP_SWIZZLE_128B,
        CU_TENSOR_MAP_L2_PROMOTION_L2_256B, CU_TENSOR_MAP_FLOAT_OOB_FILL_NONE);
}

static int h_poll_delay = POLL_DELAY, h_pdl = 1;
extern "C" void kernel_launch(void* const* d_in, const int* in_sizes, int n_in, void* d_out, int out_size) {
    const bf16 *x = (const bf16*)d_in[0], *mem0 = (const bf16*)d_in[1], *wq = (const bf16*)d_in[2], *wk = (const bf16*)d_in[3], *wv = (const bf16*)d_in[4],
               *wo = (const bf16*)d_in[5], *wg = (const bf16*)d_in[8], *wu = (const bf16*)d_in[9], *wd = (const bf16*)d_in[10], *gw = (const bf16*)d_in[11];
    static EncodeFn enc = nullptr;
    if (!enc) {
        void* fn = nullptr; cudaDriverEntryPointQueryResult qr;
        cudaGetDriverEntryPoint("cuTensorMapEncodeTiled", &fn, cudaEnableDefault, &qr);
        enc = (EncodeFn)fn;
        cudaFuncSetAttribute(rec_kernel, cudaFuncAttributeMaxDynamicSharedMemorySize, R_SMEM);
        cudaFuncSetAttribute(gemm_kernel, cudaFuncAttributeMaxDynamicSharedMemorySize, G_SMEM);
    }
    CUtensorMap tmX, tmWq, tmWk, tmWv, tmWo;
    {
        cuuint64_t dims[3] = {64, S_TOK, 10}, strides[2] = {DM * 2, 128};
        cuuint32_t box[3] = {64, 32, 5}, es[3] = {1, 1, 1};
        enc(&tmX, CU_TENSOR_MAP_DATA_TYPE_BFLOAT16, 3, (void*)x, dims, strides, box, es, CU_TENSOR_MAP_INTERLEAVE_NONE, CU_TENSOR_MAP_SWIZZLE_128B,
            CU_TENSOR_MAP_L2_PROMOTION_L2_256B, CU_TENSOR_MAP_FLOAT_OOB_FILL_NONE);
    }
    make_map(enc, &tmWq, wq, 4096, DM, 64, 160);
    make_map(enc, &tmWk, wk, 4096, DM, 64, 160);
    make_map(enc, &tmWv, wv, 4096, DM, 64, 160);
    make_map(enc, &tmWo, wo, DM, 4096, 64, 128);
    cudaStream_t st = cudaStreamPerThread;
    cudaLaunchConfig_t cfg = {};
    cfg.gridDim = dim3(96); cfg.blockDim = dim3(384); cfg.dynamicSmemBytes = R_SMEM; cfg.stream = st;
    cudaLaunchAttribute at[1];
    at[0].id = cudaLaunchAttributeClusterDimension; at[0].val.clusterDim.x = 3; at[0].val.clusterDim.y = 1; at[0].val.clusterDim.z = 1;
    cfg.attrs = at; cfg.numAttrs = 1;
    cudaLaunchKernelEx(&cfg, rec_kernel, tmX, tmWq, tmWk, tmWv, tmWo, mem0, h_poll_delay);
    CUtensorMap gX, gWg, gWu, gWo, gWd;
    make_map(enc, &gX, x, DM, S_TOK, 64, 256);
    make_map(enc, &gWg, wg, FF, DM, 64, 64);
    make_map(enc, &gWu, wu, FF, DM, 64, 64);
    make_map(enc, &gWo, wo, DM, 4096, 64, 64);
    make_map(enc, &gWd, wd, DM, FF, 64, 64);
    cudaLaunchConfig_t cg = {};
    cg.gridDim = dim3(132); cg.blockDim = dim3(384); cg.dynamicSmemBytes = G_SMEM; cg.stream = st;
    cudaLaunchAttribute ag[1];
    ag[0].id = cudaLaunchAttributeProgrammaticStreamSerialization; ag[0].val.programmaticStreamSerializationAllowed = 1;
    cg.attrs = ag; cg.numAttrs = h_pdl;
    cudaLaunchKernelEx(&cg, gemm_kernel, gX, gWg, gWu, gWo, gWd, x, gw, (bf16*)d_out);
}
```
